```python
import torch

def _softmax(x, axis=-1):
    return torch.softmax(x, dim=axis)
def _gelu(x):
    return torch.nn.functional.gelu(x, approximate="tanh")
def _silu(x):
    return torch.nn.functional.silu(x)
def _sigmoid(x):
    return torch.sigmoid(x)
def _layernorm(x, axis=-1, eps=1e-5):
    m = x.mean(dim=axis, keepdim=True)
    v = x.var(dim=axis, keepdim=True, unbiased=False)
    return (x - m) / torch.sqrt(v + eps)
def _scatter_add(tgt, idx, src, axis=0):
    return tgt.clone().index_add_(axis, idx, src)
def _segment_sum(src, seg, n):
    out = torch.zeros((n,) + src.shape[1:], dtype=src.dtype)
    return out.index_add_(0, seg, src)
def _pad(x, pw):
    flat = tuple(v for pair in reversed(pw) for v in pair)
    return torch.nn.functional.pad(x, flat)

kernel_name = 'concat_heads__sliding_block__mha_block__prompt'

def setup_inputs():

    _w = (lambda a: (lambda t: t.to(torch.bfloat16) if t.is_floating_point() else t)(torch.as_tensor(a)))
    def _A_setup():
        B, S, D = 1, 2048, 448
        return {
            "x": _w((lambda *s: torch.randn(*s, dtype=torch.bfloat16) * 0.2)(B, S, D)),
            "wqkv": _w((lambda *s: torch.randn(*s, dtype=torch.bfloat16) * 0.8)(D, 3 * D)),
            "wo": _w((lambda *s: torch.randn(*s, dtype=torch.bfloat16) * 3.2)(D, D)),
        }
    _A_in = _A_setup()

    def _B_setup():
        B, S, D, H = 1, 2048, 448, 16
        return {
            "x": _w((lambda *s: torch.randn(*s, dtype=torch.bfloat16) * 0.2)(B, S, D)),
            "wqkv": _w((lambda *s: torch.randn(*s, dtype=torch.bfloat16) * 0.8)(D, 3 * D)),
            "wo": _w((lambda *s: torch.randn(*s, dtype=torch.bfloat16) * 3.2)(D, D)),
        }
    _B_in = _B_setup()

    return {
        "A_x": _A_in["x"],
        "A_wqkv": _A_in["wqkv"],
        "A_wo": _A_in["wo"],
        "B_x": _B_in["x"],
        "B_wqkv": _B_in["wqkv"],
        "B_wo": _B_in["wo"],
    }

def reference(A_x, A_wqkv, A_wo, B_x, B_wqkv, B_wo):
    def _A_ref(x, wqkv, wo):
        B, S, D = x.shape
        H = 16; Dh = D // H; W = 256
        qkv = (lambda x, *d: x.permute(*d))((x @ wqkv).reshape(B, S, 3, H, Dh), 2, 0, 3, 1, 4)
        q, k, v = qkv[0], qkv[1], qkv[2]
        scores = torch.einsum("bhqd,bhkd->bhqk", q, k) * (Dh ** -0.5)
        idx = torch.arange(S)
        mask = (idx[:, None] - idx[None, :] >= 0) & (idx[:, None] - idx[None, :] < W)
        scores = torch.where(mask[None, None], scores, -1e9)
        p = _softmax(scores, axis=-1)
        o = torch.einsum("bhqk,bhkd->bhqd", p, v)
        return (lambda x, *d: x.permute(*d))(o, 0, 2, 1, 3).reshape(B, S, D) @ wo

    def _B_ref(x, wqkv, wo):
        B, S, D = x.shape
        H = 16
        Dh = D // H
        qkv = (lambda x, *d: x.permute(*d))((x @ wqkv).reshape(B, S, 3, H, Dh), 2, 0, 3, 1, 4)
        q, k, v = qkv[0], qkv[1], qkv[2]
        scores = torch.einsum("bhqd,bhkd->bhqk", q, k) * (Dh ** -0.5)
        p = _softmax(scores, axis=-1)
        o = torch.einsum("bhqk,bhkd->bhqd", p, v)
        return (lambda x, *d: x.permute(*d))(o, 0, 2, 1, 3).reshape(B, S, D) @ wo

    a = _A_ref(A_x, A_wqkv, A_wo)
    b = _B_ref(B_x, B_wqkv, B_wo)
    return torch.concatenate([a, b], axis=-1)
```

```cpp
#include <cuda_runtime.h>
#include <cuda_bf16.h>
#include <cuda.h>
#include <stdint.h>

namespace {

constexpr int SEQ = 2048, DM = 448, NH = 16, DH = 28;

__device__ __align__(1024) uint8_t g_qkv[2 * 3 * NH * SEQ * 64];
__device__ __align__(1024) __nv_bfloat16 g_o[2 * SEQ * DM];

__device__ __forceinline__ uint32_t s2u(const void* p) { return (uint32_t)__cvta_generic_to_shared(p); }
__device__ __forceinline__ void mbar_init(uint32_t b, int c) { asm volatile("mbarrier.init.shared.b64 [%0], %1;" ::"r"(b), "r"(c)); }
__device__ __forceinline__ void mbar_expect(uint32_t b, uint32_t n) {
  asm volatile("mbarrier.arrive.expect_tx.shared.b64 _, [%0], %1;" ::"r"(b), "r"(n) : "memory");
}
__device__ __forceinline__ void mbar_arrive(uint32_t b) { asm volatile("mbarrier.arrive.shared.b64 _, [%0];" ::"r"(b) : "memory"); }
__device__ __forceinline__ bool mbar_try(uint32_t b, uint32_t ph) {
  uint32_t ok;
  asm volatile("{.reg .pred p; mbarrier.try_wait.parity.shared.b64 p, [%1], %2; selp.u32 %0, 1, 0, p;}"
               : "=r"(ok) : "r"(b), "r"(ph) : "memory");
  return ok;
}
__device__ __forceinline__ void mbar_wait(uint32_t b, uint32_t ph) {
  if (mbar_try(b, ph)) return;
  int it = 0;
  while (!mbar_try(b, ph)) { if (++it > (1 << 22)) __trap(); }
}
__device__ __forceinline__ void tma2d(uint32_t dst, const CUtensorMap* m, int c0, int c1, uint32_t bar) {
  asm volatile("cp.async.bulk.tensor.2d.shared::cluster.global.mbarrier::complete_tx::bytes [%0], [%1, {%3, %4}], [%2];"
               ::"r"(dst), "l"((uint64_t)m), "r"(bar), "r"(c0), "r"(c1) : "memory");
}
__device__ __forceinline__ void bulk_ld(uint32_t dst, const void* src, uint32_t bytes, uint32_t bar) {
  asm volatile("cp.async.bulk.shared::cluster.global.mbarrier::complete_tx::bytes [%0], [%1], %2, [%3];"
               ::"r"(dst), "l"(src), "r"(bytes), "r"(bar) : "memory");
}
__device__ __forceinline__ void bulk_st(void* dst, uint32_t src, uint32_t bytes) {
  asm volatile("cp.async.bulk.global.shared::cta.bulk_group [%0], [%1], %2;" ::"l"(dst), "r"(src), "r"(bytes) : "memory");
}
__device__ __forceinline__ void bar_sync(int id, int n) { asm volatile("bar.sync %0, %1;" ::"r"(id), "r"(n) : "memory"); }
__device__ __forceinline__ bool bar_red_or(int id, int n, bool v) {
  uint32_t r;
  asm volatile("{.reg .pred p, q; setp.ne.u32 q, %3, 0; bar.red.or.pred p, %1, %2, q; selp.u32 %0, 1, 0, p;}"
               : "=r"(r) : "r"(id), "r"(n), "r"((uint32_t)v) : "memory");
  return r;
}
__device__ __forceinline__ bool release_last(uint32_t cnt) {
  uint32_t old;
  asm volatile("atom.shared.inc.u32 %0, [%1], 3;" : "=r"(old) : "r"(cnt) : "memory");
  return old == 3;
}
__device__ __forceinline__ void fence_async_smem() { asm volatile("fence.proxy.async.shared::cta;" ::: "memory"); }
#define WG_FENCE() asm volatile("wgmma.fence.sync.aligned;" ::: "memory")
#define WG_COMMIT() asm volatile("wgmma.commit_group.sync.aligned;" ::: "memory")
#define WG_WAIT(n) asm volatile("wgmma.wait_group.sync.aligned %0;" ::"n"(n) : "memory")
__device__ __forceinline__ uint64_t mkdesc(uint32_t addr, uint32_t lbo, uint32_t sbo, uint32_t swz) {
  return (uint64_t)((addr & 0x3FFFF) >> 4) | ((uint64_t)(lbo >> 4) << 16) | ((uint64_t)(sbo >> 4) << 32) | ((uint64_t)swz << 62);
}
template <int N> __device__ __forceinline__ void pin(float (&a)[N]) {
#pragma unroll
  for (int i = 0; i < N; i++) asm volatile("" : "+f"(a[i])::"memory");
}
__device__ __forceinline__ uint32_t pack_bf16(float lo, float hi) {
  uint32_t r;
  asm("cvt.rn.bf16x2.f32 %0, %1, %2;" : "=r"(r) : "f"(hi), "f"(lo));
  return r;
}
__device__ __forceinline__ float ex2(float x) {
  float r;
  asm("ex2.approx.ftz.f32 %0, %1;" : "=f"(r) : "f"(x));
  return r;
}
__device__ __forceinline__ void sts32(uint32_t a, uint32_t v) { asm volatile("st.shared.u32 [%0], %1;" ::"r"(a), "r"(v) : "memory"); }
__device__ __forceinline__ void sts64(uint32_t a, uint32_t x, uint32_t y) {
  asm volatile("st.shared.v2.u32 [%0], {%1, %2};" ::"r"(a), "r"(x), "r"(y) : "memory");
}

__device__ __forceinline__ void wgmma_n168_ss(float (&d)[84], uint64_t da, uint64_t db, int acc) {
  asm volatile("{.reg .pred p; setp.ne.b32 p, %86, 0;\n"
    "wgmma.mma_async.sync.aligned.m64n168k16.f32.bf16.bf16 {%0,%1,%2,%3,%4,%5,%6,%7,%8,%9,%10,%11,%12,%13,%14,%15,%16,%17,%18,%19,%20,%21,%22,%23,%24,%25,%26,%27,%28,%29,%30,%31,%32,%33,%34,%35,%36,%37,%38,%39,%40,%41,%42,%43,%44,%45,%46,%47,%48,%49,%50,%51,%52,%53,%54,%55,%56,%57,%58,%59,%60,%61,%62,%63,%64,%65,%66,%67,%68,%69,%70,%71,%72,%73,%74,%75,%76,%77,%78,%79,%80,%81,%82,%83}, %84, %85, p, 1, 1, 0, 1;}"
    : "+f"(d[0]),"+f"(d[1]),"+f"(d[2]),"+f"(d[3]),"+f"(d[4]),"+f"(d[5]),"+f"(d[6]),"+f"(d[7]),"+f"(d[8]),"+f"(d[9]),"+f"(d[10]),"+f"(d[11]),"+f"(d[12]),"+f"(d[13]),"+f"(d[14]),"+f"(d[15]),"+f"(d[16]),"+f"(d[17]),"+f"(d[18]),"+f"(d[19]),"+f"(d[20]),"+f"(d[21]),"+f"(d[22]),"+f"(d[23]),"+f"(d[24]),"+f"(d[25]),"+f"(d[26]),"+f"(d[27]),"+f"(d[28]),"+f"(d[29]),"+f"(d[30]),"+f"(d[31]),"+f"(d[32]),"+f"(d[33]),"+f"(d[34]),"+f"(d[35]),"+f"(d[36]),"+f"(d[37]),"+f"(d[38]),"+f"(d[39]),"+f"(d[40]),"+f"(d[41]),"+f"(d[42]),"+f"(d[43]),"+f"(d[44]),"+f"(d[45]),"+f"(d[46]),"+f"(d[47]),"+f"(d[48]),"+f"(d[49]),"+f"(d[50]),"+f"(d[51]),"+f"(d[52]),"+f"(d[53]),"+f"(d[54]),"+f"(d[55]),"+f"(d[56]),"+f"(d[57]),"+f"(d[58]),"+f"(d[59]),"+f"(d[60]),"+f"(d[61]),"+f"(d[62]),"+f"(d[63]),"+f"(d[64]),"+f"(d[65]),"+f"(d[66]),"+f"(d[67]),"+f"(d[68]),"+f"(d[69]),"+f"(d[70]),"+f"(d[71]),"+f"(d[72]),"+f"(d[73]),"+f"(d[74]),"+f"(d[75]),"+f"(d[76]),"+f"(d[77]),"+f"(d[78]),"+f"(d[79]),"+f"(d[80]),"+f"(d[81]),"+f"(d[82]),"+f"(d[83])
    : "l"(da), "l"(db), "r"(acc));
}

__device__ __forceinline__ void wgmma_n112_ss(float (&d)[56], uint64_t da, uint64_t db, int acc) {
  asm volatile("{.reg .pred p; setp.ne.b32 p, %58, 0;\n"
    "wgmma.mma_async.sync.aligned.m64n112k16.f32.bf16.bf16 {%0,%1,%2,%3,%4,%5,%6,%7,%8,%9,%10,%11,%12,%13,%14,%15,%16,%17,%18,%19,%20,%21,%22,%23,%24,%25,%26,%27,%28,%29,%30,%31,%32,%33,%34,%35,%36,%37,%38,%39,%40,%41,%42,%43,%44,%45,%46,%47,%48,%49,%50,%51,%52,%53,%54,%55}, %56, %57, p, 1, 1, 0, 1;}"
    : "+f"(d[0]),"+f"(d[1]),"+f"(d[2]),"+f"(d[3]),"+f"(d[4]),"+f"(d[5]),"+f"(d[6]),"+f"(d[7]),"+f"(d[8]),"+f"(d[9]),"+f"(d[10]),"+f"(d[11]),"+f"(d[12]),"+f"(d[13]),"+f"(d[14]),"+f"(d[15]),"+f"(d[16]),"+f"(d[17]),"+f"(d[18]),"+f"(d[19]),"+f"(d[20]),"+f"(d[21]),"+f"(d[22]),"+f"(d[23]),"+f"(d[24]),"+f"(d[25]),"+f"(d[26]),"+f"(d[27]),"+f"(d[28]),"+f"(d[29]),"+f"(d[30]),"+f"(d[31]),"+f"(d[32]),"+f"(d[33]),"+f"(d[34]),"+f"(d[35]),"+f"(d[36]),"+f"(d[37]),"+f"(d[38]),"+f"(d[39]),"+f"(d[40]),"+f"(d[41]),"+f"(d[42]),"+f"(d[43]),"+f"(d[44]),"+f"(d[45]),"+f"(d[46]),"+f"(d[47]),"+f"(d[48]),"+f"(d[49]),"+f"(d[50]),"+f"(d[51]),"+f"(d[52]),"+f"(d[53]),"+f"(d[54]),"+f"(d[55])
    : "l"(da), "l"(db), "r"(acc));
}

__device__ __forceinline__ void wgmma_s64_first(float (&d)[32], uint32_t a0, uint32_t a1, uint32_t a2, uint32_t a3, uint64_t db) {
  asm volatile("wgmma.mma_async.sync.aligned.m64n64k16.f32.bf16.bf16 {%0,%1,%2,%3,%4,%5,%6,%7,%8,%9,%10,%11,%12,%13,%14,%15,%16,%17,%18,%19,%20,%21,%22,%23,%24,%25,%26,%27,%28,%29,%30,%31}, {%32,%33,%34,%35}, %36, 0, 1, 1, 0;"
    : "=f"(d[0]),"=f"(d[1]),"=f"(d[2]),"=f"(d[3]),"=f"(d[4]),"=f"(d[5]),"=f"(d[6]),"=f"(d[7]),"=f"(d[8]),"=f"(d[9]),"=f"(d[10]),"=f"(d[11]),"=f"(d[12]),"=f"(d[13]),"=f"(d[14]),"=f"(d[15]),"=f"(d[16]),"=f"(d[17]),"=f"(d[18]),"=f"(d[19]),"=f"(d[20]),"=f"(d[21]),"=f"(d[22]),"=f"(d[23]),"=f"(d[24]),"=f"(d[25]),"=f"(d[26]),"=f"(d[27]),"=f"(d[28]),"=f"(d[29]),"=f"(d[30]),"=f"(d[31])
    : "r"(a0), "r"(a1), "r"(a2), "r"(a3), "l"(db));
}

__device__ __forceinline__ void wgmma_s64_acc(float (&d)[32], uint32_t a0, uint32_t a1, uint32_t a2, uint32_t a3, uint64_t db) {
  asm volatile("wgmma.mma_async.sync.aligned.m64n64k16.f32.bf16.bf16 {%0,%1,%2,%3,%4,%5,%6,%7,%8,%9,%10,%11,%12,%13,%14,%15,%16,%17,%18,%19,%20,%21,%22,%23,%24,%25,%26,%27,%28,%29,%30,%31}, {%32,%33,%34,%35}, %36, 1, 1, 1, 0;"
    : "+f"(d[0]),"+f"(d[1]),"+f"(d[2]),"+f"(d[3]),"+f"(d[4]),"+f"(d[5]),"+f"(d[6]),"+f"(d[7]),"+f"(d[8]),"+f"(d[9]),"+f"(d[10]),"+f"(d[11]),"+f"(d[12]),"+f"(d[13]),"+f"(d[14]),"+f"(d[15]),"+f"(d[16]),"+f"(d[17]),"+f"(d[18]),"+f"(d[19]),"+f"(d[20]),"+f"(d[21]),"+f"(d[22]),"+f"(d[23]),"+f"(d[24]),"+f"(d[25]),"+f"(d[26]),"+f"(d[27]),"+f"(d[28]),"+f"(d[29]),"+f"(d[30]),"+f"(d[31])
    : "r"(a0), "r"(a1), "r"(a2), "r"(a3), "l"(db));
}

__device__ __forceinline__ void wgmma_pv(float (&d)[16], uint32_t a0, uint32_t a1, uint32_t a2, uint32_t a3, uint64_t db) {
  asm volatile("wgmma.mma_async.sync.aligned.m64n32k16.f32.bf16.bf16 {%0,%1,%2,%3,%4,%5,%6,%7,%8,%9,%10,%11,%12,%13,%14,%15}, {%16,%17,%18,%19}, %20, 1, 1, 1, 1;"
    : "+f"(d[0]),"+f"(d[1]),"+f"(d[2]),"+f"(d[3]),"+f"(d[4]),"+f"(d[5]),"+f"(d[6]),"+f"(d[7]),"+f"(d[8]),"+f"(d[9]),"+f"(d[10]),"+f"(d[11]),"+f"(d[12]),"+f"(d[13]),"+f"(d[14]),"+f"(d[15])
    : "r"(a0), "r"(a1), "r"(a2), "r"(a3), "l"(db));
}


#define P70 __uint_as_float(0x62800000u)
#define M70 __uint_as_float(0x1C800000u)
#define P40 __uint_as_float(0x53800000u)
constexpr uint32_t BF_P70 = 0x6280u, BF_M70 = 0x1C80u, BF_P40 = 0x5380u;
constexpr float QSCALE = 0.27264373542131126f;
constexpr float BETA = 88.0f;

constexpr int G_STAGES = 7, G_STAGE_BYTES = 16384 + 12288;
constexpr int G_SMEM = G_STAGES * G_STAGE_BYTES + 1024 + 256;

__global__ void __launch_bounds__(512, 1)
qkv_kernel(const __grid_constant__ CUtensorMap mxA, const __grid_constant__ CUtensorMap mwA,
           const __grid_constant__ CUtensorMap mxB, const __grid_constant__ CUtensorMap mwB) {
  extern __shared__ uint8_t smem_raw[];
  const uint32_t sb = (s2u(smem_raw) + 1023) & ~1023u;
  const uint32_t bars = sb + G_STAGES * G_STAGE_BYTES;
  const int tid = threadIdx.x, warp = tid >> 5, lane = tid & 31;
  const int br = blockIdx.x >> 6, mt = (blockIdx.x >> 3) & 7, nt = blockIdx.x & 7;
  const CUtensorMap* mx = br ? &mxB : &mxA;
  const CUtensorMap* mw = br ? &mwB : &mwA;
  auto load_chunk = [&](int kc, int st) {
    const uint32_t a = sb + st * G_STAGE_BYTES, fb = bars + 8 * st;
    mbar_expect(fb, G_STAGE_BYTES);
    tma2d(a + 16384, mw, nt * 168, kc * 32, fb);
    tma2d(a + 16384 + 4096, mw, nt * 168 + 64, kc * 32, fb);
    tma2d(a + 16384 + 8192, mw, nt * 168 + 128, kc * 32, fb);
    tma2d(a, mx, kc * 32, mt * 256, fb);
  };
  if (tid == 0) {
    for (int i = 0; i < G_STAGES; i++) { mbar_init(bars + 8 * i, 1); sts32(bars + 64 + 4 * i, 0); }
    asm volatile("fence.mbarrier_init.release.cluster;" ::: "memory");
    for (int kc = 0; kc < G_STAGES; kc++) load_chunk(kc, kc);
  }
  __syncthreads();
  const int wg = warp >> 2;
  float acc[84];
#pragma unroll
  for (int i = 0; i < 84; i++) acc[i] = 0.f;
  for (int kc = 0; kc < 14; kc++) {
    const int st = kc % G_STAGES;
    mbar_wait(bars + 8 * st, kc / G_STAGES);
    const uint32_t a = sb + st * G_STAGE_BYTES;
    const uint64_t da = mkdesc(a + wg * 4096, 16, 512, 2), db = mkdesc(a + 16384, 4096, 1024, 1);
    WG_FENCE();
    wgmma_n168_ss(acc, da, db, 1);
    wgmma_n168_ss(acc, da + 2, db + 128, 1);
    WG_COMMIT();
    WG_WAIT(1);
    if (kc > 0 && kc <= 14 - G_STAGES && (tid & 127) == 0) {
      if (release_last(bars + 64 + 4 * (kc - 1))) load_chunk(kc - 1 + G_STAGES, kc - 1);
    }
  }
  WG_WAIT(0);
  pin(acc);
  bar_sync(1, 512);
  const int g = lane >> 2, t = lane & 3, sw = (g >> 1) & 3;
  const uint32_t rowbase = sb + (wg * 64 + (warp & 3) * 16 + g) * 64;
  uint32_t off[7];
#pragma unroll
  for (int c = 0; c < 7; c++) {
    const int cc = 8 * c + 2 * t, sl = cc >= 28, dim = cc - 28 * sl;
    off[c] = rowbase + sl * 16384 + (((dim >> 3) ^ sw) << 4) + (dim & 7) * 2;
  }
#pragma unroll
  for (int p = 0; p < 3; p++) {
    const int part = (nt * 6 + 2 * p) >> 4;
    const float s0 = part == 0 ? QSCALE * M70 : part == 1 ? P70 : P40;
    const float s1 = part == 0 ? QSCALE * M70 : part == 1 ? M70 : P40;
#pragma unroll
    for (int c = 0; c < 7; c++) {
      const int i = (p * 7 + c) * 4;
      sts32(off[c] + p * 32768, pack_bf16(acc[i] * s0, acc[i + 1] * s0));
      sts32(off[c] + p * 32768 + 512, pack_bf16(acc[i + 2] * s1, acc[i + 3] * s1));
    }
    const int r = wg * 64 + (tid & 63), sl = 2 * p + ((tid >> 6) & 1);
    uint32_t w0 = 0, w1 = 0;
    if (part == 1) {
      if ((r >> 3) & 1) { w0 = BF_M70 | (BF_M70 << 16); w1 = w0; }
      else { w0 = BF_P70 | (BF_P70 << 16); w1 = BF_P70; }
    } else if (part == 2) w0 = BF_P40;
    sts64(sb + sl * 16384 + r * 64 + ((3 ^ ((r >> 1) & 3)) << 4) + 8, w0, w1);
  }
  fence_async_smem();
  bar_sync(2 + wg, 128);
  if ((tid & 127) == 0) {
#pragma unroll
    for (int sl = 0; sl < 6; sl++) {
      const int sidx = nt * 6 + sl;
      bulk_st(g_qkv + ((size_t)(br * 48 + sidx) * SEQ + mt * 256 + wg * 64) * 64, sb + sl * 16384 + wg * 4096, 4096);
    }
    asm volatile("cp.async.bulk.commit_group;" ::: "memory");
    asm volatile("cp.async.bulk.wait_group 0;" ::: "memory");
  }
}

__device__ __forceinline__ uint32_t exp2_pair_sw(float x0, float x1) {
  uint32_t w, F, E, r, sh;
  asm("cvt.pack.sat.u16.s32 %0, %1, %2;" : "=r"(w) : "r"(__float_as_uint(x1)), "r"(__float_as_uint(x0)));
  asm("lop3.b32 %0, %1, 0x01FF01FF, 0x3C003C00, 0xEA;" : "=r"(F) : "r"(w));
  asm("lop3.b32 %0, %1, 0xFE00FE00, 0x00030000, 0xEA;" : "=r"(E) : "r"(w));
  asm("fma.rn.f16x2 %0, %1, %2, %3;" : "=r"(r) : "r"(F), "r"(0x311A311Au), "r"(0xB412B412u));
  asm("fma.rn.f16x2 %0, %1, %2, %3;" : "=r"(r) : "r"(F), "r"(r), "r"(0x36123612u));
  asm("fma.rn.f16x2 %0, %1, %2, %3;" : "=r"(r) : "r"(F), "r"(r), "r"(0x3FDB3FDDu));
  asm("shf.r.wrap.b32 %0, %1, 3, 2;" : "=r"(sh) : "r"(E));
  return sh + r;
}
__device__ __forceinline__ void probs(const float (&s)[32], uint32_t (&p)[16]) {
#pragma unroll
  for (int i = 0; i < 16; i++)
    p[i] = ((i >> 1) & 1) ? exp2_pair_sw(s[2 * i], s[2 * i + 1]) : pack_bf16(ex2(s[2 * i]), ex2(s[2 * i + 1]));
}
__device__ __forceinline__ void qk(float (&s)[32], const uint32_t (&q)[8], uint64_t kd) {
  WG_FENCE();
  wgmma_s64_first(s, q[4], q[5], q[6], q[7], kd + 2);
  wgmma_s64_acc(s, q[0], q[1], q[2], q[3], kd);
  WG_COMMIT();
}
__device__ __forceinline__ void pv(float (&o)[16], const uint32_t (&p)[16], uint64_t vd) {
  WG_FENCE();
#pragma unroll
  for (int k = 0; k < 4; k++) wgmma_pv(o, p[4 * k], p[4 * k + 1], p[4 * k + 2], p[4 * k + 3], vd + k * 64);
  WG_COMMIT();
}
template <int MODE> __device__ __forceinline__ void mask_p(uint32_t (&p)[16], int rmc  ) {
  if (MODE == 0) return;
#pragma unroll
  for (int i = 0; i < 16; i++) {
    const int d = rmc + 8 * (i & 1) - 8 * (i >> 1);
    uint32_t m = d >= 1 ? 0xFFFFFFFFu : (d == 0 ? 0x0000FFFFu : 0u);
    p[i] &= (MODE == 1) ? m : ~m;
  }
}
__device__ __forceinline__ void load_q(uint32_t (&q)[8], const uint8_t* qrow  , int sw, int t) {
#pragma unroll
  for (int c = 0; c < 4; c++) {
    const uint8_t* a = qrow + ((c ^ sw) << 4) + t * 4;
    q[(c >> 1) * 4 + (c & 1) * 2] = __ldcg((const uint32_t*)a);
    q[(c >> 1) * 4 + (c & 1) * 2 + 1] = __ldcg((const uint32_t*)(a + 512));
  }
}
__device__ __forceinline__ uint32_t bias_word(float m, int t) {
  const float b = -(m + BETA);
  const float h = __bfloat162float(__float2bfloat16_rn(b));
  const float r1 = b - h;
  const float mid = __bfloat162float(__float2bfloat16_rn(r1));
  const float lo = r1 - mid;
  return t == 2 ? pack_bf16(h * M70, mid * M70) : pack_bf16(lo * M70, 126.0f * M70);
}
template <int MODE> __device__ __forceinline__ void set_ref(uint32_t (&q)[8], float (&s)[32], uint64_t kd, int rmc, int t) {
  qk(s, q, kd);
  WG_WAIT(0);
  pin(s);
  float ma[2] = {-INFINITY, -INFINITY}, mb[2] = {-INFINITY, -INFINITY};
#pragma unroll
  for (int i = 0; i < 32; i++) {
    const int h = (i >> 1) & 1, c = i >> 2;
    float v = s[i];
    if (MODE == 1 && (rmc + 8 * h - 8 * c - (i & 1)) < 0) v = -INFINITY;
    if (c & 1) mb[h] = fmaxf(mb[h], v); else ma[h] = fmaxf(ma[h], v);
  }
#pragma unroll
  for (int h = 0; h < 2; h++) {
    float m = fmaxf(ma[h], (mb[h] * P70) * P70);
    m = fmaxf(m, __shfl_xor_sync(0xffffffffu, m, 1));
    m = fmaxf(m, __shfl_xor_sync(0xffffffffu, m, 2));
    if (t >= 2) q[6 + h] = bias_word(m, t);
  }
}

__device__ __forceinline__ void slow_path(float (&o)[16], uint32_t (&q)[8], const uint8_t* kg, const uint8_t* vg, int first, int last,
                                       bool window, uint32_t buf, uint32_t bar, uint32_t& ph, int wg, int rmc, int t) {
  if (t >= 2) { q[6] = 0; q[7] = 0; }
  float m[2] = {-INFINITY, -INFINITY};
#pragma unroll
  for (int i = 0; i < 16; i++) o[i] = 0.f;
  const uint64_t kd = mkdesc(buf, 16, 512, 2), vd = mkdesc(buf + 4096, 512, 512, 2);
  for (int kt = first; kt >= last; kt--) {
    if ((threadIdx.x & 127) == 0) {
      mbar_expect(bar, 8192);
      bulk_ld(buf, kg + (size_t)kt * 4096, 4096, bar);
      bulk_ld(buf + 4096, vg + (size_t)kt * 4096, 4096, bar);
    }
    mbar_wait(bar, ph);
    ph ^= 1;
    float s[32];
    uint32_t p[16];
    qk(s, q, kd);
    WG_WAIT(0);
    pin(s);
    const int mode = !window ? 0 : (kt == first ? 1 : (kt == first - 4 ? 2 : 0));
    float mn[2] = {m[0], m[1]};
#pragma unroll
    for (int i = 0; i < 32; i++) {
      const int h = (i >> 1) & 1, c = i >> 2;
      if (c & 1) s[i] = (s[i] * P70) * P70;
      const bool le = (rmc + 8 * h - 8 * c - (i & 1)) >= 0;
      if ((mode == 1 && !le) || (mode == 2 && le)) s[i] = -INFINITY;
      mn[h] = fmaxf(mn[h], s[i]);
    }
#pragma unroll
    for (int h = 0; h < 2; h++) {
      mn[h] = fmaxf(mn[h], __shfl_xor_sync(0xffffffffu, mn[h], 1));
      mn[h] = fmaxf(mn[h], __shfl_xor_sync(0xffffffffu, mn[h], 2));
      const float al = ex2(m[h] - mn[h]);
      m[h] = mn[h];
#pragma unroll
      for (int c = 0; c < 4; c++) { o[4 * c + 2 * h] *= al; o[4 * c + 2 * h + 1] *= al; }
    }
#pragma unroll
    for (int i = 0; i < 16; i++) p[i] = pack_bf16(ex2(s[2 * i] - m[i & 1]), ex2(s[2 * i + 1] - m[i & 1]));
    pv(o, p, vd);
    WG_WAIT(0);
    pin(o);
    bar_sync(2 + wg, 128);
  }
}

__device__ __forceinline__ void store_o(const float (&o)[16], __nv_bfloat16* dst  , int lane) {
  const int t = lane & 3;
  const float l0 = __shfl_sync(0xffffffffu, o[12], (lane & ~3) | 2), l1 = __shfl_sync(0xffffffffu, o[14], (lane & ~3) | 2);
  const float i0 = 1.0f / l0, i1 = 1.0f / l1;
#pragma unroll
  for (int c = 0; c < 4; c++) {
    if (c < 3 || t < 2) {
      *(uint32_t*)(dst + 8 * c + 2 * t) = pack_bf16(o[4 * c] * i0, o[4 * c + 1] * i0);
      *(uint32_t*)(dst + 8 * DM + 8 * c + 2 * t) = pack_bf16(o[4 * c + 2] * i1, o[4 * c + 3] * i1);
    }
  }
}

constexpr int A_STAGES = 6;
constexpr int A_WINK = A_STAGES * 16384, A_WINV = A_WINK + 32768, A_SLOW = A_WINV + 32768, A_BARS = A_SLOW + 32768;
constexpr int A_SMEM = A_BARS + 1024 + 256;

__global__ void __launch_bounds__(512, 1) attn_kernel() {
  extern __shared__ uint8_t smem_raw[];
  const uint32_t sb = (s2u(smem_raw) + 1023) & ~1023u;
  const uint32_t bars = sb + A_BARS;
  const int tid = threadIdx.x, warp = tid >> 5, lane = tid & 31;
  const int head = blockIdx.x & 15, qb = blockIdx.x >> 4;
  const uint8_t* gA = g_qkv + (size_t)head * SEQ * 64;
  const uint8_t* gB = g_qkv + (size_t)(48 + head) * SEQ * 64;
  constexpr size_t PART = (size_t)NH * SEQ * 64;
  auto load_kv = [&](int s, int st) {
    mbar_expect(bars + 8 * st, 16384);
    bulk_ld(sb + st * 16384, gB + PART + (size_t)s * 8192, 8192, bars + 8 * st);
    bulk_ld(sb + st * 16384 + 8192, gB + 2 * PART + (size_t)s * 8192, 8192, bars + 8 * st);
  };
  if (tid == 0) {
    for (int i = 0; i < A_STAGES; i++) { mbar_init(bars + 8 * i, 1); sts32(bars + 64 + 4 * i, 0); }
    for (int i = 0; i < 5; i++) mbar_init(bars + 128 + 8 * i, 1);
    asm volatile("fence.mbarrier_init.release.cluster;" ::: "memory");
    {
      const int k0 = qb == 0 ? 0 : qb * 256 - 256, skip = qb == 0 ? 16384 : 0, bytes = 32768 - skip;
      mbar_expect(bars + 128, 2 * bytes);
      bulk_ld(sb + A_WINK + skip, gA + PART + (size_t)k0 * 64, bytes, bars + 128);
      bulk_ld(sb + A_WINV + skip, gA + 2 * PART + (size_t)k0 * 64, bytes, bars + 128);
    }
    for (int s = 0; s < A_STAGES; s++) load_kv(s, s);
  }
  __syncthreads();
  const int wg = warp >> 2, g = lane >> 2, t = lane & 3, sw = (g >> 1) & 3;
  const int rloc = (warp & 3) * 16 + g, row = qb * 256 + wg * 64 + rloc, rmc = rloc - 2 * t;
  uint32_t slow_ph = 0;
  float s[32], o[16];
  uint32_t q[8], p[16];
  {
    load_q(q, gA + (size_t)row * 64, sw, t);
    mbar_wait(bars + 128, 0);
    const int qt = qb * 4 + wg;
    const uint64_t kd = mkdesc(sb + A_WINK + wg * 4096, 16, 512, 2), vd = mkdesc(sb + A_WINV + wg * 4096, 512, 512, 2);
    if (qt == 0) set_ref<1>(q, s, kd + 4 * 256, rmc, t); else set_ref<0>(q, s, kd + 3 * 256, rmc, t);
#pragma unroll
    for (int i = 0; i < 16; i++) o[i] = 0.f;
    qk(s, q, kd + 4 * 256); WG_WAIT(0); pin(s); probs(s, p); mask_p<1>(p, rmc); pv(o, p, vd + 4 * 256);
    for (int j = 3; j >= 1 && qt - 4 + j >= 0; j--) {
      qk(s, q, kd + j * 256); WG_WAIT(0); pin(s); probs(s, p); pv(o, p, vd + j * 256);
    }
    if (qt >= 4) { qk(s, q, kd); WG_WAIT(0); pin(s); probs(s, p); mask_p<2>(p, rmc); pv(o, p, vd); }
    WG_WAIT(0);
    pin(o);
    const bool bad = t == 2 && !(o[12] < P40 && o[14] < P40);
    if (bar_red_or(2 + wg, 128, bad))
      slow_path(o, q, gA + PART, gA + 2 * PART, qt, qt >= 4 ? qt - 4 : 0, true, sb + A_SLOW + wg * 8192, bars + 136 + 8 * wg, slow_ph, wg, rmc, t);
    store_o(o, g_o + (size_t)row * DM + head * DH, lane);
  }
  {
    load_q(q, gB + (size_t)row * 64, sw, t);
    mbar_wait(bars, 0);
    set_ref<0>(q, s, mkdesc(sb, 16, 512, 2), rmc, t);
#pragma unroll
    for (int i = 0; i < 16; i++) o[i] = 0.f;
    int st = 0, ph = 0, prev = 0;
    for (int sidx = 0; sidx < 16; sidx++) {
      mbar_wait(bars + 8 * st, ph);
      const uint64_t kd = mkdesc(sb + st * 16384, 16, 512, 2), vd = mkdesc(sb + st * 16384 + 8192, 512, 512, 2);
      qk(s, q, kd); WG_WAIT(0); pin(s);
      if (sidx > 0 && sidx <= 16 - A_STAGES && (tid & 127) == 0) {
        if (release_last(bars + 64 + 4 * prev)) load_kv(sidx - 1 + A_STAGES, prev);
      }
      probs(s, p); pv(o, p, vd);
      qk(s, q, kd + 256); WG_WAIT(0); pin(s);
      probs(s, p); pv(o, p, vd + 256);
      prev = st;
      if (++st == A_STAGES) { st = 0; ph ^= 1; }
    }
    WG_WAIT(0);
    pin(o);
    const bool bad = t == 2 && !(o[12] < P40 && o[14] < P40);
    if (bar_red_or(2 + wg, 128, bad))
      slow_path(o, q, gB + PART, gB + 2 * PART, 31, 0, false, sb + A_SLOW + wg * 8192, bars + 136 + 8 * wg, slow_ph, wg, rmc, t);
    store_o(o, g_o + (size_t)(SEQ + row) * DM + head * DH, lane);
  }
}

constexpr int O_SMEM = 7 * 32768 + 1024 + 128;
__global__ void __launch_bounds__(288, 1)
out_kernel(const __grid_constant__ CUtensorMap mo, const __grid_constant__ CUtensorMap mwoA,
           const __grid_constant__ CUtensorMap mwoB, __nv_bfloat16* __restrict__ out) {
  extern __shared__ uint8_t smem_raw[];
  const uint32_t sb = (s2u(smem_raw) + 1023) & ~1023u;
  const uint32_t bars = sb + 7 * 32768;
  const int tid = threadIdx.x, warp = tid >> 5, lane = tid & 31;
  const int br = blockIdx.x >> 6, mt = (blockIdx.x >> 2) & 15, nt = blockIdx.x & 3;
  if (tid == 0) {
    for (int i = 0; i < 7; i++) mbar_init(bars + 8 * i, 1);
    asm volatile("fence.mbarrier_init.release.cluster;" ::: "memory");
  }
  __syncthreads();
  if (warp == 8) {
    if (lane == 0) {
      const CUtensorMap* mw = br ? &mwoB : &mwoA;
      for (int kc = 0; kc < 7; kc++) {
        const uint32_t a = sb + kc * 32768, fb = bars + 8 * kc;
        mbar_expect(fb, 32768);
        tma2d(a + 16384, mw, nt * 112, kc * 64, fb);
        tma2d(a + 16384 + 8192, mw, nt * 112 + 64, kc * 64, fb);
        tma2d(a, &mo, kc * 64, br * SEQ + mt * 128, fb);
      }
    }
    return;
  }
  const int wg = warp >> 2;
  float acc[56];
#pragma unroll
  for (int i = 0; i < 56; i++) acc[i] = 0.f;
  for (int kc = 0; kc < 7; kc++) {
    mbar_wait(bars + 8 * kc, 0);
    const uint32_t a = sb + kc * 32768;
    const uint64_t da = mkdesc(a + wg * 8192, 16, 1024, 1), db = mkdesc(a + 16384, 8192, 1024, 1);
    WG_FENCE();
#pragma unroll
    for (int ks = 0; ks < 4; ks++) wgmma_n112_ss(acc, da + 2 * ks, db + 128 * ks, 1);
    WG_COMMIT();
  }
  WG_WAIT(0);
  pin(acc);
  const int g = lane >> 2, t = lane & 3;
  __nv_bfloat16* dst = out + (size_t)(mt * 128 + wg * 64 + (warp & 3) * 16 + g) * (2 * DM) + br * DM + nt * 112 + 2 * t;
#pragma unroll
  for (int c = 0; c < 14; c++) {
    *(uint32_t*)(dst + 8 * c) = pack_bf16(acc[4 * c], acc[4 * c + 1]);
    *(uint32_t*)(dst + 8 * 2 * DM + 8 * c) = pack_bf16(acc[4 * c + 2], acc[4 * c + 3]);
  }
}

typedef CUresult (*EncodeFn)(CUtensorMap*, CUtensorMapDataType, cuuint32_t, void*, const cuuint64_t*, const cuuint64_t*,
                             const cuuint32_t*, const cuuint32_t*, CUtensorMapInterleave, CUtensorMapSwizzle,
                             CUtensorMapL2promotion, CUtensorMapFloatOOBfill);

void make_map(EncodeFn enc, CUtensorMap* m, const void* ptr, uint64_t d0, uint64_t d1, uint32_t b0, uint32_t b1, CUtensorMapSwizzle sw) {
  cuuint64_t dims[2] = {d0, d1};
  cuuint64_t strides[1] = {d0 * 2};
  cuuint32_t box[2] = {b0, b1};
  cuuint32_t es[2] = {1, 1};
  enc(m, CU_TENSOR_MAP_DATA_TYPE_BFLOAT16, 2, const_cast<void*>(ptr), dims, strides, box, es, CU_TENSOR_MAP_INTERLEAVE_NONE, sw,
      CU_TENSOR_MAP_L2_PROMOTION_L2_128B, CU_TENSOR_MAP_FLOAT_OOB_FILL_NONE);
}

}

extern "C" void kernel_launch(void* const* d_in, const int* in_sizes, int n_in, void* d_out, int out_size) {
  (void)in_sizes; (void)n_in; (void)out_size;
  void* fn = nullptr;
  cudaDriverEntryPointQueryResult qr;
  cudaGetDriverEntryPoint("cuTensorMapEncodeTiled", &fn, cudaEnableDefault, &qr);
  EncodeFn enc = (EncodeFn)fn;
  void* optr = nullptr;
  cudaGetSymbolAddress(&optr, g_o);
  CUtensorMap mxA, mwA, mxB, mwB, mo, mwoA, mwoB;
  make_map(enc, &mxA, d_in[0], DM, SEQ, 32, 256, CU_TENSOR_MAP_SWIZZLE_64B);
  make_map(enc, &mwA, d_in[1], 3 * DM, DM, 64, 32, CU_TENSOR_MAP_SWIZZLE_128B);
  make_map(enc, &mwoA, d_in[2], DM, DM, 64, 64, CU_TENSOR_MAP_SWIZZLE_128B);
  make_map(enc, &mxB, d_in[3], DM, SEQ, 32, 256, CU_TENSOR_MAP_SWIZZLE_64B);
  make_map(enc, &mwB, d_in[4], 3 * DM, DM, 64, 32, CU_TENSOR_MAP_SWIZZLE_128B);
  make_map(enc, &mwoB, d_in[5], DM, DM, 64, 64, CU_TENSOR_MAP_SWIZZLE_128B);
  make_map(enc, &mo, optr, DM, 2 * SEQ, 64, 128, CU_TENSOR_MAP_SWIZZLE_128B);
  cudaFuncSetAttribute(qkv_kernel, cudaFuncAttributeMaxDynamicSharedMemorySize, G_SMEM);
  cudaFuncSetAttribute(attn_kernel, cudaFuncAttributeMaxDynamicSharedMemorySize, A_SMEM);
  cudaFuncSetAttribute(out_kernel, cudaFuncAttributeMaxDynamicSharedMemorySize, O_SMEM);
  qkv_kernel<<<128, 512, G_SMEM>>>(mxA, mwA, mxB, mwB);
  attn_kernel<<<128, 512, A_SMEM>>>();
  out_kernel<<<128, 288, O_SMEM>>>(mo, mwoA, mwoB, (__nv_bfloat16*)d_out);
}
```

```cpp
#include <cuda_runtime.h>
#include <cuda_bf16.h>
#include <cuda.h>
#include <stdint.h>

#define SWG 0xAA
#define SPLIT 0x17F
#define LATEM 0x133
#define NLOC 4
#define LOOK 3
#define PSLEEP 100
#define WPACE 150
#define APACE 500

namespace {

constexpr int SEQ = 2048, DM = 448, NH = 16, DH = 28;

__device__ __align__(1024) uint8_t g_q[2 * NH * SEQ * 64];
__device__ __align__(1024) uint8_t g_kv[2 * NH * SEQ * 128];
__device__ __align__(1024) uint8_t g_wo[56 * 8192];
__device__ __align__(1024) uint8_t g_zero[16384];
__device__ __align__(1024) uint8_t g_o[2 * 32 * DM * 128];

__device__ __forceinline__ uint32_t s2u(const void* p) { return (uint32_t)__cvta_generic_to_shared(p); }
__device__ __forceinline__ void mbar_init(uint32_t b, int c) { asm volatile("mbarrier.init.shared.b64 [%0], %1;" ::"r"(b), "r"(c)); }
__device__ __forceinline__ void mbar_expect(uint32_t b, uint32_t n) {
  asm volatile("{.reg .pred e; elect.sync _|e, 0xffffffff;\n@e mbarrier.arrive.expect_tx.shared.b64 _, [%0], %1;}" ::"r"(b), "r"(n) : "memory");
}
__device__ __forceinline__ void mbar_arrive_e(uint32_t b) {
  asm volatile("{.reg .pred e; elect.sync _|e, 0xffffffff;\n@e mbarrier.arrive.shared.b64 _, [%0];}" ::"r"(b) : "memory");
}
__device__ __forceinline__ void mbar_arrive(uint32_t b) { asm volatile("mbarrier.arrive.shared.b64 _, [%0];" ::"r"(b) : "memory"); }
__device__ __forceinline__ void mbar_wait(uint32_t b, uint32_t ph) {
  asm volatile("{.reg .pred p; .reg .u32 i; mov.u32 i, 0;\n"
               "W%=: mbarrier.try_wait.parity.shared.b64 p, [%0], %1; add.u32 i, i, 1; setp.ge.or.u32 p, i, 262144, p; @!p bra W%=;}"
               ::"r"(b), "r"(ph) : "memory");
}
__device__ __forceinline__ void mbar_wait_hot(uint32_t b, uint32_t ph, int& budget) {
  asm volatile("{.reg .pred p;\n"
               "W%=: mbarrier.try_wait.parity.shared.b64 p, [%1], %2;\n"
               "@!p add.s32 %0, %0, -1; @!p setp.lt.s32 p, %0, 0; @!p bra W%=;\n}"
               : "+r"(budget) : "r"(b), "r"(ph) : "memory");
}
__device__ __forceinline__ bool mbar_test(uint32_t b, uint32_t ph) {
  uint32_t ok;
  asm volatile("{.reg .pred p; mbarrier.test_wait.parity.shared.b64 p, [%1], %2; selp.u32 %0, 1, 0, p;}" : "=r"(ok) : "r"(b), "r"(ph) : "memory");
  return ok;
}
__device__ __forceinline__ void mbar_wait_lazy(uint32_t b, uint32_t ph) {
#pragma unroll 1
  for (int i = 0; i < (1 << 19) && !mbar_test(b, ph); i++) __nanosleep(400);
}
__device__ __forceinline__ void tma2d(uint32_t dst, const CUtensorMap* m, int c0, int c1, uint32_t bar) {
  asm volatile("{.reg .pred e; elect.sync _|e, 0xffffffff;\n@e cp.async.bulk.tensor.2d.shared::cluster.global.mbarrier::complete_tx::bytes [%0], [%1, {%3, %4}], [%2];}"
               ::"r"(dst), "l"((uint64_t)m), "r"(bar), "r"(c0), "r"(c1) : "memory");
}
__device__ __forceinline__ void bulk_ld(uint32_t dst, const void* src, uint32_t bytes, uint32_t bar) {
  asm volatile("{.reg .pred e; elect.sync _|e, 0xffffffff;\n@e cp.async.bulk.shared::cluster.global.mbarrier::complete_tx::bytes [%0], [%1], %2, [%3];}"
               ::"r"(dst), "l"(src), "r"(bytes), "r"(bar) : "memory");
}
__device__ __forceinline__ void bulk_st(void* dst, uint32_t src, uint32_t bytes) {
  asm volatile("{.reg .pred e; elect.sync _|e, 0xffffffff;\n@e cp.async.bulk.global.shared::cta.bulk_group [%0], [%1], %2;}" ::"l"(dst), "r"(src), "r"(bytes) : "memory");
}
__device__ __forceinline__ void bar_sync(int id, int n) { asm volatile("bar.sync %0, %1;" ::"r"(id), "r"(n) : "memory"); }
__device__ __forceinline__ void fence_async_smem() { asm volatile("fence.proxy.async.shared::cta;" ::: "memory"); }
#define WG_FENCE() asm volatile("wgmma.fence.sync.aligned;" ::: "memory")
#define WG_COMMIT() asm volatile("wgmma.commit_group.sync.aligned;" ::: "memory")
#define WG_WAIT(n) asm volatile("wgmma.wait_group.sync.aligned %0;" ::"n"(n) : "memory")
__host__ __device__ constexpr uint32_t mkdesc(uint32_t addr) { return ((addr & 0x3FFFF) >> 4) | 0x10000u; }
template <int N> __device__ __forceinline__ void pin(uint32_t (&a)[N]) {
#pragma unroll
  for (int i = 0; i < N; i++) asm volatile("" : "+r"(a[i])::"memory");
}
template <int N> __device__ __forceinline__ void pin(float (&a)[N]) {
#pragma unroll
  for (int i = 0; i < N; i++) asm volatile("" : "+f"(a[i])::"memory");
}
__device__ __forceinline__ uint32_t pack_bf16(float lo, float hi) {
  uint32_t r;
  asm("cvt.rn.bf16x2.f32 %0, %1, %2;" : "=r"(r) : "f"(hi), "f"(lo));
  return r;
}
__device__ __forceinline__ float ex2(float x) {
  float r;
  asm("ex2.approx.ftz.f32 %0, %1;" : "=f"(r) : "f"(x));
  return r;
}
__device__ __forceinline__ void sts32(uint32_t a, uint32_t v) { asm volatile("st.shared.u32 [%0], %1;" ::"r"(a), "r"(v) : "memory"); }
__device__ __forceinline__ void stsf4(uint32_t a, const float* v) {
  asm volatile("st.shared.v4.f32 [%0], {%1,%2,%3,%4};" ::"r"(a), "f"(v[0]), "f"(v[1]), "f"(v[2]), "f"(v[3]) : "memory");
}
__device__ __forceinline__ void ldsf4(uint32_t a, float* v) {
  asm volatile("ld.shared.v4.f32 {%0,%1,%2,%3}, [%4];" : "=f"(v[0]), "=f"(v[1]), "=f"(v[2]), "=f"(v[3]) : "r"(a) : "memory");
}

__device__ __forceinline__ void wgmma_g(float (&d)[32], uint32_t da, uint32_t db) {
  asm volatile("{.reg .b64 da, db; mov.b64 da, {%32, 0x80000020}; mov.b64 db, {%33, 0x40000040};\n"
    "wgmma.mma_async.sync.aligned.m64n64k16.f32.bf16.bf16 {%0,%1,%2,%3,%4,%5,%6,%7,%8,%9,%10,%11,%12,%13,%14,%15,%16,%17,%18,%19,%20,%21,%22,%23,%24,%25,%26,%27,%28,%29,%30,%31}, da, db, 1, 1, 1, 0, 1;}"
    : "+f"(d[0]),"+f"(d[1]),"+f"(d[2]),"+f"(d[3]),"+f"(d[4]),"+f"(d[5]),"+f"(d[6]),"+f"(d[7]),"+f"(d[8]),"+f"(d[9]),"+f"(d[10]),"+f"(d[11]),"+f"(d[12]),"+f"(d[13]),"+f"(d[14]),"+f"(d[15]),"+f"(d[16]),"+f"(d[17]),"+f"(d[18]),"+f"(d[19]),"+f"(d[20]),"+f"(d[21]),"+f"(d[22]),"+f"(d[23]),"+f"(d[24]),"+f"(d[25]),"+f"(d[26]),"+f"(d[27]),"+f"(d[28]),"+f"(d[29]),"+f"(d[30]),"+f"(d[31])
    : "r"(da), "r"(db));
}

__device__ __forceinline__ void wgmma_g0(float (&d)[32], uint32_t da, uint32_t db) {
  asm volatile("{.reg .b64 da, db; mov.b64 da, {%32, 0x80000020}; mov.b64 db, {%33, 0x40000040};\n"
    "wgmma.mma_async.sync.aligned.m64n64k16.f32.bf16.bf16 {%0,%1,%2,%3,%4,%5,%6,%7,%8,%9,%10,%11,%12,%13,%14,%15,%16,%17,%18,%19,%20,%21,%22,%23,%24,%25,%26,%27,%28,%29,%30,%31}, da, db, 0, 1, 1, 0, 1;}"
    : "=f"(d[0]),"=f"(d[1]),"=f"(d[2]),"=f"(d[3]),"=f"(d[4]),"=f"(d[5]),"=f"(d[6]),"=f"(d[7]),"=f"(d[8]),"=f"(d[9]),"=f"(d[10]),"=f"(d[11]),"=f"(d[12]),"=f"(d[13]),"=f"(d[14]),"=f"(d[15]),"=f"(d[16]),"=f"(d[17]),"=f"(d[18]),"=f"(d[19]),"=f"(d[20]),"=f"(d[21]),"=f"(d[22]),"=f"(d[23]),"=f"(d[24]),"=f"(d[25]),"=f"(d[26]),"=f"(d[27]),"=f"(d[28]),"=f"(d[29]),"=f"(d[30]),"=f"(d[31])
    : "r"(da), "r"(db));
}

__device__ __forceinline__ void wgmma_g(float (&d)[52], uint32_t da, uint32_t db) {
  asm volatile("{.reg .b64 da, db; mov.b64 da, {%52, 0x80000020}; mov.b64 db, {%53, 0x40000040};\n"
    "wgmma.mma_async.sync.aligned.m64n104k16.f32.bf16.bf16 {%0,%1,%2,%3,%4,%5,%6,%7,%8,%9,%10,%11,%12,%13,%14,%15,%16,%17,%18,%19,%20,%21,%22,%23,%24,%25,%26,%27,%28,%29,%30,%31,%32,%33,%34,%35,%36,%37,%38,%39,%40,%41,%42,%43,%44,%45,%46,%47,%48,%49,%50,%51}, da, db, 1, 1, 1, 0, 1;}"
    : "+f"(d[0]),"+f"(d[1]),"+f"(d[2]),"+f"(d[3]),"+f"(d[4]),"+f"(d[5]),"+f"(d[6]),"+f"(d[7]),"+f"(d[8]),"+f"(d[9]),"+f"(d[10]),"+f"(d[11]),"+f"(d[12]),"+f"(d[13]),"+f"(d[14]),"+f"(d[15]),"+f"(d[16]),"+f"(d[17]),"+f"(d[18]),"+f"(d[19]),"+f"(d[20]),"+f"(d[21]),"+f"(d[22]),"+f"(d[23]),"+f"(d[24]),"+f"(d[25]),"+f"(d[26]),"+f"(d[27]),"+f"(d[28]),"+f"(d[29]),"+f"(d[30]),"+f"(d[31]),"+f"(d[32]),"+f"(d[33]),"+f"(d[34]),"+f"(d[35]),"+f"(d[36]),"+f"(d[37]),"+f"(d[38]),"+f"(d[39]),"+f"(d[40]),"+f"(d[41]),"+f"(d[42]),"+f"(d[43]),"+f"(d[44]),"+f"(d[45]),"+f"(d[46]),"+f"(d[47]),"+f"(d[48]),"+f"(d[49]),"+f"(d[50]),"+f"(d[51])
    : "r"(da), "r"(db));
}

__device__ __forceinline__ void wgmma_g0(float (&d)[52], uint32_t da, uint32_t db) {
  asm volatile("{.reg .b64 da, db; mov.b64 da, {%52, 0x80000020}; mov.b64 db, {%53, 0x40000040};\n"
    "wgmma.mma_async.sync.aligned.m64n104k16.f32.bf16.bf16 {%0,%1,%2,%3,%4,%5,%6,%7,%8,%9,%10,%11,%12,%13,%14,%15,%16,%17,%18,%19,%20,%21,%22,%23,%24,%25,%26,%27,%28,%29,%30,%31,%32,%33,%34,%35,%36,%37,%38,%39,%40,%41,%42,%43,%44,%45,%46,%47,%48,%49,%50,%51}, da, db, 0, 1, 1, 0, 1;}"
    : "=f"(d[0]),"=f"(d[1]),"=f"(d[2]),"=f"(d[3]),"=f"(d[4]),"=f"(d[5]),"=f"(d[6]),"=f"(d[7]),"=f"(d[8]),"=f"(d[9]),"=f"(d[10]),"=f"(d[11]),"=f"(d[12]),"=f"(d[13]),"=f"(d[14]),"=f"(d[15]),"=f"(d[16]),"=f"(d[17]),"=f"(d[18]),"=f"(d[19]),"=f"(d[20]),"=f"(d[21]),"=f"(d[22]),"=f"(d[23]),"=f"(d[24]),"=f"(d[25]),"=f"(d[26]),"=f"(d[27]),"=f"(d[28]),"=f"(d[29]),"=f"(d[30]),"=f"(d[31]),"=f"(d[32]),"=f"(d[33]),"=f"(d[34]),"=f"(d[35]),"=f"(d[36]),"=f"(d[37]),"=f"(d[38]),"=f"(d[39]),"=f"(d[40]),"=f"(d[41]),"=f"(d[42]),"=f"(d[43]),"=f"(d[44]),"=f"(d[45]),"=f"(d[46]),"=f"(d[47]),"=f"(d[48]),"=f"(d[49]),"=f"(d[50]),"=f"(d[51])
    : "r"(da), "r"(db));
}

__device__ __forceinline__ void wgmma_op(float (&d)[32], uint32_t da, uint32_t db) {
  asm volatile("{.reg .b64 da, db; mov.b64 da, {%32, 0x40000040}; mov.b64 db, {%33, 0x40000040};\n"
    "wgmma.mma_async.sync.aligned.m64n64k16.f32.bf16.bf16 {%0,%1,%2,%3,%4,%5,%6,%7,%8,%9,%10,%11,%12,%13,%14,%15,%16,%17,%18,%19,%20,%21,%22,%23,%24,%25,%26,%27,%28,%29,%30,%31}, da, db, 1, 1, 1, 1, 1;}"
    : "+f"(d[0]),"+f"(d[1]),"+f"(d[2]),"+f"(d[3]),"+f"(d[4]),"+f"(d[5]),"+f"(d[6]),"+f"(d[7]),"+f"(d[8]),"+f"(d[9]),"+f"(d[10]),"+f"(d[11]),"+f"(d[12]),"+f"(d[13]),"+f"(d[14]),"+f"(d[15]),"+f"(d[16]),"+f"(d[17]),"+f"(d[18]),"+f"(d[19]),"+f"(d[20]),"+f"(d[21]),"+f"(d[22]),"+f"(d[23]),"+f"(d[24]),"+f"(d[25]),"+f"(d[26]),"+f"(d[27]),"+f"(d[28]),"+f"(d[29]),"+f"(d[30]),"+f"(d[31])
    : "r"(da), "r"(db));
}

__device__ __forceinline__ void wgmma_op(float (&d)[24], uint32_t da, uint32_t db) {
  asm volatile("{.reg .b64 da, db; mov.b64 da, {%24, 0x40000040}; mov.b64 db, {%25, 0x40000040};\n"
    "wgmma.mma_async.sync.aligned.m64n48k16.f32.bf16.bf16 {%0,%1,%2,%3,%4,%5,%6,%7,%8,%9,%10,%11,%12,%13,%14,%15,%16,%17,%18,%19,%20,%21,%22,%23}, da, db, 1, 1, 1, 1, 1;}"
    : "+f"(d[0]),"+f"(d[1]),"+f"(d[2]),"+f"(d[3]),"+f"(d[4]),"+f"(d[5]),"+f"(d[6]),"+f"(d[7]),"+f"(d[8]),"+f"(d[9]),"+f"(d[10]),"+f"(d[11]),"+f"(d[12]),"+f"(d[13]),"+f"(d[14]),"+f"(d[15]),"+f"(d[16]),"+f"(d[17]),"+f"(d[18]),"+f"(d[19]),"+f"(d[20]),"+f"(d[21]),"+f"(d[22]),"+f"(d[23])
    : "r"(da), "r"(db));
}

__device__ __forceinline__ void wgmma_op0(float (&d)[32], uint32_t da, uint32_t db) {
  asm volatile("{.reg .b64 da, db; mov.b64 da, {%32, 0x40000040}; mov.b64 db, {%33, 0x40000040};\n"
    "wgmma.mma_async.sync.aligned.m64n64k16.f32.bf16.bf16 {%0,%1,%2,%3,%4,%5,%6,%7,%8,%9,%10,%11,%12,%13,%14,%15,%16,%17,%18,%19,%20,%21,%22,%23,%24,%25,%26,%27,%28,%29,%30,%31}, da, db, 0, 1, 1, 1, 1;}"
    : "=f"(d[0]),"=f"(d[1]),"=f"(d[2]),"=f"(d[3]),"=f"(d[4]),"=f"(d[5]),"=f"(d[6]),"=f"(d[7]),"=f"(d[8]),"=f"(d[9]),"=f"(d[10]),"=f"(d[11]),"=f"(d[12]),"=f"(d[13]),"=f"(d[14]),"=f"(d[15]),"=f"(d[16]),"=f"(d[17]),"=f"(d[18]),"=f"(d[19]),"=f"(d[20]),"=f"(d[21]),"=f"(d[22]),"=f"(d[23]),"=f"(d[24]),"=f"(d[25]),"=f"(d[26]),"=f"(d[27]),"=f"(d[28]),"=f"(d[29]),"=f"(d[30]),"=f"(d[31])
    : "r"(da), "r"(db));
}

__device__ __forceinline__ void wgmma_op0(float (&d)[24], uint32_t da, uint32_t db) {
  asm volatile("{.reg .b64 da, db; mov.b64 da, {%24, 0x40000040}; mov.b64 db, {%25, 0x40000040};\n"
    "wgmma.mma_async.sync.aligned.m64n48k16.f32.bf16.bf16 {%0,%1,%2,%3,%4,%5,%6,%7,%8,%9,%10,%11,%12,%13,%14,%15,%16,%17,%18,%19,%20,%21,%22,%23}, da, db, 0, 1, 1, 1, 1;}"
    : "=f"(d[0]),"=f"(d[1]),"=f"(d[2]),"=f"(d[3]),"=f"(d[4]),"=f"(d[5]),"=f"(d[6]),"=f"(d[7]),"=f"(d[8]),"=f"(d[9]),"=f"(d[10]),"=f"(d[11]),"=f"(d[12]),"=f"(d[13]),"=f"(d[14]),"=f"(d[15]),"=f"(d[16]),"=f"(d[17]),"=f"(d[18]),"=f"(d[19]),"=f"(d[20]),"=f"(d[21]),"=f"(d[22]),"=f"(d[23])
    : "r"(da), "r"(db));
}

__device__ __forceinline__ void wgmma_pv(float (&d)[16], uint32_t a0, uint32_t a1, uint32_t a2, uint32_t a3, uint32_t db) {
  asm volatile("{.reg .b64 db; mov.b64 db, {%20, 0x80000020};\n"
    "wgmma.mma_async.sync.aligned.m64n32k16.f32.bf16.bf16 {%0,%1,%2,%3,%4,%5,%6,%7,%8,%9,%10,%11,%12,%13,%14,%15}, {%16,%17,%18,%19}, db, 1, 1, 1, 1;}"
    : "+f"(d[0]),"+f"(d[1]),"+f"(d[2]),"+f"(d[3]),"+f"(d[4]),"+f"(d[5]),"+f"(d[6]),"+f"(d[7]),"+f"(d[8]),"+f"(d[9]),"+f"(d[10]),"+f"(d[11]),"+f"(d[12]),"+f"(d[13]),"+f"(d[14]),"+f"(d[15])
    : "r"(a0), "r"(a1), "r"(a2), "r"(a3), "r"(db));
}

__device__ __forceinline__ void wgmma_pv0(float (&d)[16], uint32_t a0, uint32_t a1, uint32_t a2, uint32_t a3, uint32_t db) {
  asm volatile("{.reg .b64 db; mov.b64 db, {%20, 0x80000020};\n"
    "wgmma.mma_async.sync.aligned.m64n32k16.f32.bf16.bf16 {%0,%1,%2,%3,%4,%5,%6,%7,%8,%9,%10,%11,%12,%13,%14,%15}, {%16,%17,%18,%19}, db, 0, 1, 1, 1;}"
    : "=f"(d[0]),"=f"(d[1]),"=f"(d[2]),"=f"(d[3]),"=f"(d[4]),"=f"(d[5]),"=f"(d[6]),"=f"(d[7]),"=f"(d[8]),"=f"(d[9]),"=f"(d[10]),"=f"(d[11]),"=f"(d[12]),"=f"(d[13]),"=f"(d[14]),"=f"(d[15])
    : "r"(a0), "r"(a1), "r"(a2), "r"(a3), "r"(db));
}

__device__ __forceinline__ void wgmma_s64_first_rs(uint32_t (&d)[32], uint32_t a0, uint32_t a1, uint32_t a2, uint32_t a3, uint32_t db) {
  asm volatile("{.reg .b64 db; mov.b64 db, {%36, 0x80000020};\n"
    "wgmma.mma_async.sync.aligned.m64n64k16.f32.bf16.bf16 {%0,%1,%2,%3,%4,%5,%6,%7,%8,%9,%10,%11,%12,%13,%14,%15,%16,%17,%18,%19,%20,%21,%22,%23,%24,%25,%26,%27,%28,%29,%30,%31}, {%32,%33,%34,%35}, db, 0, 1, 1, 0;}"
    : "=r"(d[0]),"=r"(d[1]),"=r"(d[2]),"=r"(d[3]),"=r"(d[4]),"=r"(d[5]),"=r"(d[6]),"=r"(d[7]),"=r"(d[8]),"=r"(d[9]),"=r"(d[10]),"=r"(d[11]),"=r"(d[12]),"=r"(d[13]),"=r"(d[14]),"=r"(d[15]),"=r"(d[16]),"=r"(d[17]),"=r"(d[18]),"=r"(d[19]),"=r"(d[20]),"=r"(d[21]),"=r"(d[22]),"=r"(d[23]),"=r"(d[24]),"=r"(d[25]),"=r"(d[26]),"=r"(d[27]),"=r"(d[28]),"=r"(d[29]),"=r"(d[30]),"=r"(d[31])
    : "r"(a0), "r"(a1), "r"(a2), "r"(a3), "r"(db));
}

__device__ __forceinline__ void wgmma_s64_acc_rs(uint32_t (&d)[32], uint32_t a0, uint32_t a1, uint32_t a2, uint32_t a3, uint32_t db) {
  asm volatile("{.reg .b64 db; mov.b64 db, {%36, 0x80000020};\n"
    "wgmma.mma_async.sync.aligned.m64n64k16.f32.bf16.bf16 {%0,%1,%2,%3,%4,%5,%6,%7,%8,%9,%10,%11,%12,%13,%14,%15,%16,%17,%18,%19,%20,%21,%22,%23,%24,%25,%26,%27,%28,%29,%30,%31}, {%32,%33,%34,%35}, db, 1, 1, 1, 0;}"
    : "+r"(d[0]),"+r"(d[1]),"+r"(d[2]),"+r"(d[3]),"+r"(d[4]),"+r"(d[5]),"+r"(d[6]),"+r"(d[7]),"+r"(d[8]),"+r"(d[9]),"+r"(d[10]),"+r"(d[11]),"+r"(d[12]),"+r"(d[13]),"+r"(d[14]),"+r"(d[15]),"+r"(d[16]),"+r"(d[17]),"+r"(d[18]),"+r"(d[19]),"+r"(d[20]),"+r"(d[21]),"+r"(d[22]),"+r"(d[23]),"+r"(d[24]),"+r"(d[25]),"+r"(d[26]),"+r"(d[27]),"+r"(d[28]),"+r"(d[29]),"+r"(d[30]),"+r"(d[31])
    : "r"(a0), "r"(a1), "r"(a2), "r"(a3), "r"(db));
}


#define P70 __uint_as_float(0x62800000u)
#define M70 __uint_as_float(0x1C800000u)
#define LMIN __uint_as_float(0x2B800000u)
#define LMAX __uint_as_float(0x5F800000u)
constexpr uint32_t BF_P70 = 0x6280u, BF_M70 = 0x1C80u, BF_ONE = 0x3F80u;
constexpr float QSCALE = 0.27264373542131126f;
constexpr float BETA = 37.0f;

__device__ __forceinline__ float shfl_idx(float v, int src) {
  float r;
  asm volatile("shfl.sync.idx.b32 %0, %1, %2, 31, 0xffffffff;" : "=f"(r) : "f"(v), "r"(src));
  return r;
}
struct ExpC { uint32_t k  , c3  ; };
template <uint32_t PART = 0xFFFF, uint32_t LATE = 0, uint32_t PACK = 0>
__device__ __forceinline__ void probs(uint32_t (&s)[32], uint32_t (&p)[16], const ExpC& ec) {
#pragma unroll
  for (int i = 0; i < 16; i++) {
    if ((PACK >> i) & 1) asm("cvt.rn.bf16x2.f32 %0, %1, %2;" : "=r"(p[i]) : "r"(s[2 * i + 1]), "r"(s[2 * i]));
    if (!((PART >> i) & 1)) continue;
    uint32_t &A = s[2 * i], &B = s[2 * i + 1], &R = s[2 * i + 1 - (i & 1)];
    if ((SWG >> (i >> 1)) & 1) {
      asm("cvt.pack.sat.u16.s32 %0, %0, %1;" : "+r"(B) : "r"(A));
      asm("lop3.b32 %0, %1, 0x01FF01FF, %2, 0xEA;" : "=r"(A) : "r"(B), "r"(ec.k));
      asm("and.b32 %0, %1, 0xFE00FE00;" : "=r"(p[i]) : "r"(B));
      asm("fma.rn.f16x2 %0, %1, %2, %3;" : "=r"(B) : "r"(A), "r"(ec.c3), "r"(0x94089408u));
      asm("fma.rn.f16x2 %0, %1, %0, %2;" : "+r"(B) : "r"(A), "r"(0x16071607u));
      asm("fma.rn.f16x2 %0, %1, %2, %3;" : "=r"(R) : "r"(A), "r"(B), "r"(0x1EDE1EDEu));
      asm("{.reg .b32 t; shr.u32 t, %0, 2; add.u32 %0, t, %1;}" : "+r"(p[i]) : "r"(R));
    } else {
      asm("ex2.approx.ftz.f32 %0, %0;" : "+r"(A));
      asm("ex2.approx.ftz.f32 %0, %0;" : "+r"(B));
      if (!((LATE >> i) & 1)) asm("cvt.rn.bf16x2.f32 %0, %1, %2;" : "=r"(p[i]) : "r"(B), "r"(A));
    }
  }
#pragma unroll
  for (int i = 0; i < 16; i++) {
    if ((((PART & ~LATE) | PACK) >> i) & 1) asm volatile("" : "+r"(p[i])::"memory");
    if ((LATE >> i) & 1) asm volatile("" : "+r"(s[2 * i]), "+r"(s[2 * i + 1])::"memory");
  }
}
__device__ __forceinline__ void qk(uint32_t (&s)[32], const uint32_t (&q)[8], uint32_t kd) {
  wgmma_s64_first_rs(s, q[0], q[1], q[2], q[3], kd + 2);
  wgmma_s64_acc_rs(s, q[4], q[5], q[6], q[7], kd);
  WG_COMMIT();
}
__device__ __forceinline__ void pv(float (&o)[16], const uint32_t (&p)[16], uint32_t kd) {
#pragma unroll
  for (int k = 0; k < 4; k++) wgmma_pv(o, p[4 * k], p[4 * k + 1], p[4 * k + 2], p[4 * k + 3], kd + 256 + k * 64);
  WG_COMMIT();
}
__device__ __forceinline__ void pv0(float (&o)[16], const uint32_t (&p)[16], uint32_t kd) {
  wgmma_pv0(o, p[0], p[1], p[2], p[3], kd + 256);
#pragma unroll
  for (int k = 1; k < 4; k++) wgmma_pv(o, p[4 * k], p[4 * k + 1], p[4 * k + 2], p[4 * k + 3], kd + 256 + k * 64);
  WG_COMMIT();
}
__device__ __forceinline__ void set_ref(uint32_t (&s)[32], uint32_t (&q)[8], int e, int ct, bool diag) {
  const int rm = ((ct >> 5) & 3) * 16 + ((ct >> 2) & 7) - 2 * (ct & 3);
  if (diag) {
#pragma unroll
    for (int h = 0; h < 2; h++) {
      const float k0 = shfl_idx(__uint_as_float(s[2 * h]), ct & 28);
      const uint32_t f0 = __float_as_uint(k0), f1 = __float_as_uint((SWG & 1) ? (k0 * P70) * P70 : (k0 * M70) * M70);
#pragma unroll
      for (int i = 0; i < 16; i++)
        if (rm + 8 * h - 8 * (i >> 1) - (i & 1) < 0) s[(i >> 1) * 4 + 2 * h + (i & 1)] = (((SWG >> (i >> 1)) ^ SWG) & 1) ? f1 : f0;
    }
  }
#pragma unroll
  for (int h = 0; h < 2; h++) {
    int mx[2];
    bool init[2] = {false, false};
#pragma unroll
    for (int c = 0; c < 8; c++) {
      const int ty = (SWG >> c) & 1, v0 = s[4 * c + 2 * h], v1 = s[4 * c + 2 * h + 1];
      mx[ty] = init[ty] ? __vimax3_s32(mx[ty], v0, v1) : max(v0, v1);
      init[ty] = true;
    }
    float m = fmaxf(__int_as_float(mx[0]), (__int_as_float(mx[1]) * P70) * P70);
    m = fmaxf(m, __shfl_xor_sync(0xffffffffu, m, 1));
    m = fmaxf(m, __shfl_xor_sync(0xffffffffu, m, 2));
    const uint32_t bw = pack_bf16(fmaf(m, -M70, -BETA * M70), 63.0f * M70);
    if ((ct & 3) == 2 - 2 * e) q[2 + h] = bw;
    const float bs = __uint_as_float(bw << 16), b1 = bs * P70, b2 = (bs + 62.998f * M70) * M70;
#pragma unroll
    for (int i = 0; i < 16; i++) asm("add.f32 %0, %0, %1;" : "+r"(s[(i >> 1) * 4 + 2 * h + (i & 1)]) : "f"(((SWG >> (i >> 1)) & 1) ? b2 : b1));
  }
}
__device__ __forceinline__ void mask_p(uint32_t (&p)[16], int w4, uint32_t tri, uint32_t f) {
#pragma unroll
  for (int b = 0; b < 4; b++) {
    const uint32_t le = b <= w4 ? ~f : f, lt = b < w4 ? ~f : f, dg = b == w4 ? tri ^ f : lt;
    p[4 * b] &= dg; p[4 * b + 1] &= le; p[4 * b + 2] &= lt; p[4 * b + 3] &= dg;
  }
#pragma unroll
  for (int i = 0; i < 16; i++) asm volatile("" : "+r"(p[i])::"memory");
}
__device__ __forceinline__ uint32_t mul_bf16x2(uint32_t a, uint32_t b) {
  uint32_t r;
  asm("mul.rn.bf16x2 %0, %1, %2;" : "=r"(r) : "r"(a), "r"(b));
  return r;
}
__device__ __forceinline__ float rcp(float x) {
  float r;
  asm("rcp.approx.ftz.f32 %0, %1;" : "=f"(r) : "f"(x));
  return r;
}
__device__ __forceinline__ void hmma(float* d, const uint32_t* a, uint32_t b0, uint32_t b1) {
  asm volatile("mma.sync.aligned.m16n8k16.row.col.f32.bf16.bf16.f32 {%0,%1,%2,%3}, {%4,%5,%6,%7}, {%8,%9}, {%0,%1,%2,%3};"
               : "+f"(d[0]), "+f"(d[1]), "+f"(d[2]), "+f"(d[3]) : "r"(a[0]), "r"(a[1]), "r"(a[2]), "r"(a[3]), "r"(b0), "r"(b1));
}
__device__ __forceinline__ uint32_t ldg16(const uint8_t* p) { return __ldcg((const unsigned short*)p); }
__device__ __noinline__ void slow_path(float* out, uint32_t qa, const uint8_t* kvg, int row  ,
                                          bool window, int lane) {
  const int g = lane >> 2, t = lane & 3, sw = (g >> 1) & 3;
  float o[16];
  uint32_t q[8];
  asm volatile("ldmatrix.sync.aligned.m8n8.x4.shared.b16 {%0,%1,%2,%3}, [%4];" : "=r"(q[0]), "=r"(q[1]), "=r"(q[2]), "=r"(q[3]) : "r"(qa) : "memory");
  asm volatile("ldmatrix.sync.aligned.m8n8.x4.shared.b16 {%0,%1,%2,%3}, [%4];" : "=r"(q[4]), "=r"(q[5]), "=r"(q[6]), "=r"(q[7]) : "r"(qa ^ 32) : "memory");
  float m[2] = {-INFINITY, -INFINITY};
#pragma unroll
  for (int i = 0; i < 16; i++) o[i] = 0.f;
  const int first = window ? row >> 4 : SEQ / 16 - 1, last = (window && first > 16) ? first - 16 : 0;
#pragma unroll 1
  for (int kb = first; kb >= last; kb--) {
    float s[8];
    const uint8_t* blk = kvg + (size_t)(kb >> 2) * 8192 + (kb & 3) * 1024;
    const uint8_t* kr = blk + g * 64 + t * 4;
#pragma unroll
    for (int c = 0; c < 2; c++) {
      s[4 * c] = s[4 * c + 1] = s[4 * c + 2] = s[4 * c + 3] = 0.f;
      const uint8_t* r = kr + c * 512;
      hmma(s + 4 * c, q, __ldcg((const uint32_t*)(r + ((0 ^ sw) << 4))), __ldcg((const uint32_t*)(r + ((1 ^ sw) << 4))));
      hmma(s + 4 * c, q + 4, __ldcg((const uint32_t*)(r + ((2 ^ sw) << 4))), __ldcg((const uint32_t*)(r + ((3 ^ sw) << 4))));
    }
    float mn[2] = {m[0], m[1]};
#pragma unroll
    for (int i = 0; i < 8; i++) {
      const int h = (i >> 1) & 1, c = i >> 2;
      if ((SWG >> ((kb & 3) * 2 + c)) & 1) s[i] = (s[i] * P70) * P70;
      const int d = row + 8 * h - (kb * 16 + 8 * c + 2 * t + (i & 1));
      if (window && (d < 0 || d >= 256)) s[i] = -INFINITY;
      mn[h] = fmaxf(mn[h], s[i]);
    }
#pragma unroll
    for (int h = 0; h < 2; h++) {
      mn[h] = fmaxf(mn[h], __shfl_xor_sync(0xffffffffu, mn[h], 1));
      mn[h] = fmaxf(mn[h], __shfl_xor_sync(0xffffffffu, mn[h], 2));
      const float al = ex2(m[h] - mn[h]);
      m[h] = mn[h];
#pragma unroll
      for (int c = 0; c < 4; c++) { o[4 * c + 2 * h] *= al; o[4 * c + 2 * h + 1] *= al; }
    }
    uint32_t p[4];
#pragma unroll
    for (int i = 0; i < 4; i++) p[i] = pack_bf16(ex2(s[2 * i] - m[i & 1]), ex2(s[2 * i + 1] - m[i & 1]));
    const uint8_t* vr = blk + 4096 + t * 128 + g * 2;
#pragma unroll
    for (int c = 0; c < 4; c++) {
      const uint8_t* r = vr + ((c ^ t) << 4);
      hmma(o + 4 * c, p, ldg16(r) | (ldg16(r + 64) << 16), ldg16(r + 512) | (ldg16(r + 576) << 16));
    }
  }
#pragma unroll
  for (int i = 0; i < 16; i++) out[i] = o[i];
}

constexpr uint32_t G_STAGE = 28672, SLOT = 24576, WIN = 49152, OFF_Q = 98304, OFF_STASH = 131072,
                   OFF_RING = 172032, OFF_QB = OFF_RING + 32768, OFF_BAR = 229376;
constexpr int SMEM_BYTES = OFF_BAR + 1024;
constexpr uint32_t sb = 1024, bars = sb + OFF_BAR;
constexpr uint32_t B_GFULL = 0, B_GEMPTY = 56, B_RFULL = 112, B_REMPTY = 144, B_FIN = 176, B_OPA = 208, B_OPB = 264, B_WIN = 320,
                   B_EPI = 328, B_LOCAL = 336, B_WFREE = 344, B_END = 360, B_FINB = 368, B_NEAR = 400, B_GLAST = 408,
                   B_OPFREE = 480, B_OPW = 536, B_EPIKV = 592, B_WIN2 = 608, B_PACK = 616, B_CONST = 624, B_RING4 = 632,
                   W_SEEN = 640, B_ALLFIN = 648, B_TICK = 656, B_PACKED = 664, B_L0 = 672;

__device__ unsigned g_flag[128 * 32];
__device__ unsigned g_cnt_o[2 * 32 * 32];
__device__ unsigned g_cnt_w[32];
__device__ unsigned g_epoch[128];

__device__ __forceinline__ void release_gpu() { asm volatile("fence.proxy.async.global; fence.acq_rel.gpu;" ::: "memory"); }
__device__ __forceinline__ void signal(unsigned* c) {
  asm volatile("{.reg .pred e; elect.sync _|e, 0xffffffff;\n@e red.relaxed.gpu.global.add.u32 [%0], 1;}" ::"l"(c) : "memory");
}
__device__ __forceinline__ void publish(unsigned* f, int level, unsigned v) {
  release_gpu();
  const int lane = threadIdx.x & 31;
  __syncwarp();
  if (lane < 8) asm volatile("st.relaxed.gpu.global.u32 [%0], %1;" ::"l"(f + level * 8 + lane), "r"(v) : "memory");
}
__device__ __forceinline__ unsigned ld_flag(const unsigned* f) {
  unsigned v;
  asm volatile("ld.relaxed.gpu.global.u32 %0, [%1];" : "=r"(v) : "l"(f) : "memory");
  return v;
}
__device__ __forceinline__ unsigned poll_mask(const unsigned* f, unsigned target, unsigned need) {
  unsigned v0 = ld_flag(f), m;
  __nanosleep(PSLEEP);
  unsigned v1 = ld_flag(f);
  __nanosleep(PSLEEP);
  int it = 0;
#pragma unroll 1
  do {
    const unsigned v2 = ld_flag(f);
    m = __ballot_sync(0xffffffffu, (int)(v0 - target) >= 0);
    v0 = v1;
    v1 = v2;
  } while ((m & need) != need && ++it < (1 << 19));
  asm volatile("fence.proxy.async.global;" ::: "memory");
  return m;
}
__device__ __forceinline__ void poll_lazy(const unsigned* f, unsigned target) {
#pragma unroll 1
  for (int it = 0; it < (1 << 19) && __any_sync(0xffffffffu, (int)(ld_flag(f) - target) < 0); it++) __nanosleep(500);
  asm volatile("fence.proxy.async.global;" ::: "memory");
}
__device__ __forceinline__ void ldsm4(uint32_t& a, uint32_t& b, uint32_t& c, uint32_t& d, uint32_t addr) {
  asm volatile("ldmatrix.sync.aligned.m8n8.x4.shared.b16 {%0,%1,%2,%3}, [%4];" : "=r"(a), "=r"(b), "=r"(c), "=r"(d) : "r"(addr) : "memory");
}
__device__ __forceinline__ void stsm4(uint32_t addr, uint32_t a, uint32_t b, uint32_t c, uint32_t d) {
  asm volatile("stmatrix.sync.aligned.m8n8.x4.shared.b16 [%0], {%1,%2,%3,%4};" ::"r"(addr), "r"(a), "r"(b), "r"(c), "r"(d) : "memory");
}
__device__ __forceinline__ void stsm4t(uint32_t addr, uint32_t a, uint32_t b, uint32_t c, uint32_t d) {
  asm volatile("stmatrix.sync.aligned.m8n8.x4.trans.shared.b16 [%0], {%1,%2,%3,%4};" ::"r"(addr), "r"(a), "r"(b), "r"(c), "r"(d) : "memory");
}
__device__ __forceinline__ void tma3d(uint32_t dst, const CUtensorMap* m, int c0, int c1, int c2, uint32_t bar) {
  asm volatile("{.reg .pred e; elect.sync _|e, 0xffffffff;\n@e cp.async.bulk.tensor.3d.shared::cluster.global.mbarrier::complete_tx::bytes [%0], [%1, {%3, %4, %5}], [%2];}"
               ::"r"(dst), "l"((uint64_t)m), "r"(bar), "r"(c0), "r"(c1), "r"(c2) : "memory");
}
#define INIT_FENCE() asm volatile("fence.mbarrier_init.release.cluster;" ::: "memory")
#define BULK_COMMIT() asm volatile("cp.async.bulk.commit_group;" ::: "memory")
#define BULK_WAIT(n) asm volatile("cp.async.bulk.wait_group %0;" ::"n"(n) : "memory")
__device__ __forceinline__ int cold_tid() {
  int v;
  asm volatile("mov.u32 %0, %%tid.x;" : "=r"(v));
  return v;
}
__device__ __forceinline__ uint32_t lm_offset(int tid) {
  return (((tid >> 5) & 3) * 16 + (tid & 15)) * 64 + ((((tid >> 4) & 1) ^ ((tid >> 1) & 3)) << 4);
}
struct Maps { CUtensorMap x[2], w[2], wo[2]; const uint8_t* in[6]; uint8_t* out; };

__device__ __forceinline__ void wait_tick() {
  const uint32_t par = mbar_test(bars + B_TICK, 0);
#pragma unroll 1
  for (int i = 0; i < 10 && !mbar_test(bars + B_TICK, par); i++) __nanosleep(50);
}
__device__ __forceinline__ int cold_cta() {
  int v;
  asm volatile("mov.u32 %0, %%ctaid.x;" : "=r"(v));
  return v;
}
__host__ __device__ constexpr uint32_t qa_of(int br, int w) { return sb + OFF_Q + (w & 1) * (br ? 8192 : 16384) + ((w >> 1) + (br ? 0 : 2)) * 4096; }
__device__ __forceinline__ const unsigned* flag_of(int cta, int b, int l) {
  return g_flag + (b * 64 + (l < 16 ? (l & 7) * 8 + (cta & 7) : cta & 63)) * 32 + (l < 16 ? l & 8 : 16);
}

__host__ __device__ constexpr uint32_t wo_addr(int b, int c, int h) {
  return !b ? sb + c * SLOT + h * 8192 : c >= 3 ? sb + (c - 3) * SLOT + h * 8192 : sb + OFF_RING + ((c | h) ? 2 * c + h : 6) * 8192;
}
__device__ __forceinline__ bool vote_bad(bool v) {
  uint32_t r;
  asm volatile("{.reg .pred p, q; setp.ne.u32 q, %1, 0; bar.red.or.pred p, 6, 384, q; selp.u32 %0, 1, 0, p;}"
               : "=r"(r) : "r"((uint32_t)v) : "memory");
  return r;
}
__device__ __forceinline__ void validate() {
  const int ct = cold_tid(), cta = cold_cta();
  const uint32_t va = sb + 16384 + (ct & 127) * 32 + (ct & 28);
#pragma unroll 1
  for (uint32_t ph = 0; ph <= 4096; ph++) {
    uint32_t v[14];
    int budget = 1 << 18;
#pragma unroll
    for (int c = 0; c < 7; c++) {
      mbar_wait_hot(bars + B_OPB + 8 * c, ph & 1, budget);
      asm volatile("ld.shared.u32 %0, [%2]; ld.shared.u32 %1, [%2+4096];" : "=r"(v[2 * c]), "=r"(v[2 * c + 1]) : "r"(va + c * SLOT) : "memory");
    }
    uint32_t mx = 0;
#pragma unroll
    for (int c = 0; c < 7; c++) mx = __vimax3_u32(mx, v[2 * c], v[2 * c + 1]);
    if (!vote_bad(mx == 0xFFFFFFFFu) || ph == 4096) break;
    if ((ct >> 5) == 19) {
      fence_async_smem();
#pragma unroll 1
      for (int c = 0; c < 7; c++) {
        mbar_expect(bars + B_OPB + 8 * c, 8192);
        bulk_ld(sb + c * SLOT + 16384, g_o + (size_t)(32 + ((cta >> 3) & 7) * 4 + (cta & 3)) * (DM * 128) + c * 8192, 8192, bars + B_OPB + 8 * c);
      }
    }
  }
}
template <int H> __device__ __forceinline__ void proj(int b, uint8_t* out, bool leader) {
  constexpr int NG = H ? 6 : 8;
  float acc[NG * 4];
  int budget = 1 << 18;
  const uint32_t bo = bars + (b ? B_OPB : B_OPA), bw = bars + (b ? B_OPW : B_OPA);
  mbar_wait_hot(bars + B_ALLFIN, 0, budget);
#pragma unroll
  for (int c = 0; c < 7; c++) {
    mbar_wait_hot(bw + 8 * c, 0, budget);
    mbar_wait_hot(bo + 8 * c, 0, budget);
    const uint32_t da = mkdesc(sb + c * SLOT + 16384), db = b ? mkdesc(wo_addr(1, c, H)) : mkdesc(wo_addr(0, c, H));
    WG_FENCE();
    if (c == 0) wgmma_op0(acc, da, db); else wgmma_op(acc, da, db);
#pragma unroll
    for (int ks = 1; ks < 4; ks++) wgmma_op(acc, da + 128 * ks, db + 128 * ks);
    WG_COMMIT();
    if (c) {
      WG_WAIT(1);
      if (!b && leader) mbar_arrive(bars + B_OPFREE + 8 * (c - 1));
    }
  }
  const int ct = cold_tid(), lane = ct & 31, w4 = (ct >> 5) & 3, r0 = lane >> 3, cx = lane & 7, cta = cold_cta();
  const uint32_t stg = sb + (4 + b) * SLOT + H * 8192 + w4 * 2048;
  uint32_t wa = stg + (lane & 15) * 128 + (((lane >> 4) ^ (lane & 7)) << 4), ra = stg + r0 * 128 + ((cx ^ r0) << 4);
  uint8_t* dst = out + (size_t)((((cta >> 3) & 7) * 4 + (cta & 3)) * 64 + w4 * 16 + r0) * (4 * DM) + b * (2 * DM) +
                 (((cta >> 2) & 1) + 2 * (cta >> 6)) * 224 + H * 128 + cx * 16;
  asm volatile("" : "+r"(wa), "+r"(ra), "+l"(dst));
  WG_WAIT(0);
  pin(acc);
  if (!b && leader) mbar_arrive(bars + B_OPFREE + 48);
#pragma unroll 1
  for (uint32_t ph = 1;; ph++) {
#pragma unroll
    for (int c = 0; c < NG; c += 2)
      stsm4(wa ^ (c << 4), pack_bf16(acc[4 * c], acc[4 * c + 1]), pack_bf16(acc[4 * c + 2], acc[4 * c + 3]),
            pack_bf16(acc[4 * c + 4], acc[4 * c + 5]), pack_bf16(acc[4 * c + 6], acc[4 * c + 7]));
    __syncwarp();
    if (cx < NG) {
#pragma unroll
      for (int i = 0; i < 4; i++) {
        float v[4];
        ldsf4((ra ^ ((i & 1) << 6)) + i * 512, v);
        *(float4*)(dst + (size_t)i * 4 * (4 * DM)) = make_float4(v[0], v[1], v[2], v[3]);
      }
    }
    if (!b || !vote_bad(false) || ph > 4096) break;
#pragma unroll
    for (int i = 0; i < NG * 4; i++) acc[i] = 0.f;
#pragma unroll 1
    for (int c = 0; c < 7; c++) {
      mbar_wait(bo + 8 * c, ph & 1);
      const uint32_t da = mkdesc(sb + c * SLOT + 16384), db = mkdesc(wo_addr(1, c, H));
      pin(acc);
      WG_FENCE();
#pragma unroll
      for (int ks = 0; ks < 4; ks++) wgmma_op(acc, da + 128 * ks, db + 128 * ks);
      WG_COMMIT();
      WG_WAIT(0);
      pin(acc);
    }
  }
}

template <int FULL> __device__ __forceinline__ void finish(float (&o)[16], bool release, uint32_t rel) {
  const int BR = cold_cta() >> 6;
  const int ct = cold_tid(), lane = ct & 31, w4 = (ct >> 5) & 3, wg = ct >> 7;
  const int e = FULL ? BR ^ 1 : (wg & 1), tb = 2 - 2 * e;
  const uint32_t qa = FULL ? sb + OFF_QB + wg * 4096 : qa_of(BR, wg);
  const int col = (lane >> 4) * 8 + (lane & 7);
  const uint32_t sw = ((2 * w4 + ((lane >> 3) & 1)) ^ (col & 7)) << 4;
  uint32_t a0 = qa + ((col + 4 * e) & 31) * 128 + sw, a1 = qa + ((col + 16 + 4 * e) & 31) * 128 + sw, src = (lane & ~3) | tb;
  asm volatile("" : "+r"(a0), "+r"(a1), "+r"(src));
  WG_WAIT(0);
  pin(o);
  if (release) mbar_arrive(rel);
  const bool bad = (ct & 3) == tb && !(o[12] < LMAX && o[14] < LMAX && o[12] > LMIN && o[14] > LMIN);
  if (__any_sync(0xffffffffu, bad)) {
    const int cta = cold_cta(), qt = ((cta >> 3) & 7) * 4 + (FULL ? wg : (wg >> 1) + (BR ? 0 : 2));
    poll_mask(flag_of(cta, FULL, lane), g_epoch[cta] + 1, 0xFF00u);
    float tmp[16];
    slow_path(tmp, qa + lm_offset(ct), g_kv + (size_t)(FULL * 16 + (cta & 7) * 2 + e) * (SEQ * 128), qt * 64 + w4 * 16 + (lane >> 2), !FULL, lane);
#pragma unroll
    for (int i = 0; i < 16; i++) o[i] = tmp[i];
  }
  const float i0 = rcp(shfl_idx(o[12], src)), i1 = rcp(shfl_idx(o[14], src));
  bar_sync(2 + wg, 128);
  stsm4t(a0, pack_bf16(o[0] * i0, o[1] * i0), pack_bf16(o[2] * i1, o[3] * i1), pack_bf16(o[4] * i0, o[5] * i0),
         pack_bf16(o[6] * i1, o[7] * i1));
  stsm4t(a1, pack_bf16(o[8] * i0, o[9] * i0), pack_bf16(o[10] * i1, o[11] * i1), pack_bf16(o[12] * i0, o[13] * i0),
         pack_bf16(o[14] * i1, o[15] * i1));
  fence_async_smem();
  __syncwarp();
  if (lane == 0) mbar_arrive(bars + (FULL ? B_FINB : B_FIN) + 8 * wg);
  if (FULL && lane == 0) mbar_arrive(bars + B_ALLFIN);
}

constexpr uint32_t KR = mkdesc(sb + OFF_RING + 4096), KL = mkdesc(sb + 16384);
__device__ __forceinline__ void load_q(uint32_t (&q)[8], uint32_t qa) {
  const uint32_t a = qa + lm_offset(cold_tid());
  ldsm4(q[0], q[1], q[2], q[3], a ^ 32);
  ldsm4(q[4], q[5], q[6], q[7], a);
}
__device__ __forceinline__ uint32_t win_diag(int wg) { return mkdesc(sb + (wg & 1) * WIN + (4 + (wg >> 1)) * 8192); }
__device__ __forceinline__ bool win_head(int wg) { return (blockIdx.x >> 3) == 8 && wg < 2; }
#define RSTEP(ks, PV, pp, kv, pc) do { WG_FENCE(); qk(s, q, ks); PV(o, pp, kv); WG_WAIT(1); pin(s); \
    probs<SPLIT, LATEM>(s, pc, ec); WG_WAIT(0); pin(o); mbar_wait_hot(bars + B_EPI, 0, budget);   \
    pin(s); probs<0xFFFF ^ SPLIT, 0, LATEM>(s, pc, ec); } while (0)

__device__ __forceinline__ void window_task(uint32_t (&s)[32], uint32_t (&q)[8], const ExpC& ec, bool leader, int cw) {
  const int BR = blockIdx.x >> 6;
  float o[16];
  uint32_t p0[16], p1[16];
  const int ct = cold_tid(), w4 = cw & 3, wg = cw >> 2;
  const int hi = wg >> 1, dd = ((ct >> 2) & 7) - 2 * (ct & 3);
  const uint32_t tri = dd >= 1 ? 0xFFFFFFFFu : (dd == 0 ? 0x0000FFFFu : 0u);
  const bool head = win_head(wg);
  const uint32_t kdg = win_diag(wg), k0 = head ? kdg : kdg - 512, k1 = head ? kdg - 512 : kdg;
  int budget = 1 << 18;
  set_ref(s, q, wg & 1, ct, head);
  probs(s, p0, ec);
  if (head) mask_p(p0, w4, tri, 0u);
  RSTEP(k1, pv0, p0, k0, p1);
  mask_p(p1, w4, tri, 0u);
  RSTEP(kdg - 1024, pv, p1, k1, p0);
  if (!BR && !hi) mbar_wait(bars + B_WIN, 0);
  RSTEP(kdg - 1536, pv, p0, kdg - 1024, p1);
  if (!BR) mbar_wait(bars + (hi ? B_WIN : B_WIN2), 0);
  RSTEP(kdg - 2048, pv, p1, kdg - 1536, p0);
  mask_p(p0, w4, tri, 0xFFFFFFFFu);
  mbar_wait(bars + B_RFULL, BR & NLOC);
  load_q(q, sb + OFF_QB + wg * 4096);
  if (BR) asm volatile("ld.shared.v2.u32 {%0, %1}, [%2];" : "=r"(q[2]), "=r"(q[3]) : "r"(sb + OFF_STASH + 32768 + ct * 8) : "memory");
  WG_FENCE(); pv(o, p0, kdg - 2048); qk(s, q, KR);
  finish<0>(o, !BR && leader, bars + B_LOCAL);
  pin(s);
}

template <bool LOC>
__device__ __forceinline__ void ring_task(uint32_t (&s)[32], uint32_t (&q)[8], float (&o)[16], const ExpC& ec, bool leader, int wg) {
  const int BR = LOC ? 1 : blockIdx.x >> 6;
  uint32_t p0[16], p1[16];
  const uint32_t kl = KL + wg * 512;
  uint32_t par = LOC ? 0 : BR & NLOC;
  int budget = 1 << 18, it = LOC ? NLOC : 8 - (NLOC + 1) * BR;
  if (LOC) { load_q(q, sb + OFF_QB + wg * 4096); WG_FENCE(); qk(s, q, kl); WG_WAIT(0); pin(s); }
  if (LOC || !BR) set_ref(s, q, BR ^ 1, cold_tid(), false);
  probs(s, p0, ec);
#define STEP(u, pp, pc) do { WG_FENCE(); qk(s, q, KR + (u) * 512); pv(o, pp, KR + (u) * 512 - 512); WG_WAIT(1); pin(s); \
    probs<SPLIT, LATEM>(s, pc, ec); if ((u) == 3) par ^= 1; \
    WG_WAIT(0); pin(o); if (leader) mbar_arrive(bars + B_REMPTY + 8 * (u)); \
    mbar_wait_hot(bars + B_RFULL + 8 * (((u) + 1) & 3), par, budget); pin(s); \
    probs<0xFFFF ^ SPLIT, 0, LATEM>(s, pc, ec); } while (0)
  if (LOC) {
    const uint32_t k1 = KL + (wg ^ 1) * 512, k2 = KL + (wg ^ 2) * 512, k3 = KL + (wg ^ 3) * 512;
    mbar_wait(bars + B_EPI, 0);
    RSTEP(k1, pv0, p0, kl, p1);
    RSTEP(k2, pv, p1, k1, p0);
    RSTEP(k3, pv, p0, k2, p1);
    mbar_wait(bars + B_RFULL, 0);
    RSTEP(KR, pv, p1, k3, p0);
    if (leader) mbar_arrive(bars + B_LOCAL);
  }
  pin(o);
  if (leader) mbar_arrive(bars + B_REMPTY);
  mbar_wait_hot(bars + B_RFULL + 8, par, budget);
#pragma unroll 1
  while (true) {
    STEP(1, p0, p1);
    STEP(2, p1, p0);
    STEP(3, p0, p1);
    if (--it == 0) break;
    STEP(0, p1, p0);
  }
  if (LOC) {
    const int ct = cold_tid();
    asm volatile("st.shared.v2.u32 [%0], {%1, %2};" ::"r"(sb + OFF_STASH + 32768 + ct * 8), "r"(q[2]), "r"(q[3]) : "memory");
    mbar_wait(bars + B_WIN, 0);
    load_q(q, qa_of(1, wg));
    WG_FENCE(); pv(o, p1, KR - 512); qk(s, q, win_diag(wg) - (win_head(wg) ? 0 : 512));
    WG_WAIT(1);
    pin(o);
#pragma unroll
    for (int i = 0; i < 4; i++) stsf4(sb + OFF_STASH + ct * 16 + i * 8192, o + 4 * i);
    WG_WAIT(0);
    pin(s);
  } else {
    WG_FENCE(); pv(o, p1, KR - 512);
    finish<1>(o, false, 0);
  }
#undef STEP
}

__device__ __forceinline__ void attention(bool leader, int warp) {
  const int wg = warp >> 2;
  ExpC ec;
  asm volatile("ld.shared.v2.u32 {%0, %1}, [%2];" : "=r"(ec.k), "=r"(ec.c3) : "r"(bars + B_CONST));
  uint32_t s[32], q[8];
  if (blockIdx.x >> 6) {
    float o[16];
    ring_task<true>(s, q, o, ec, leader, wg);
  } else {
    load_q(q, qa_of(0, wg));
    WG_FENCE(); qk(s, q, win_diag(wg) - 512); WG_WAIT(0); pin(s);
  }
  window_task(s, q, ec, leader, warp);
  float o[16];
#pragma unroll
  for (int i = 0; i < 16; i++) o[i] = 0.f;
  if (blockIdx.x >> 6) {
    const int ct = cold_tid();
#pragma unroll
    for (int i = 0; i < 4; i++) ldsf4(sb + OFF_STASH + ct * 16 + i * 8192, o + 4 * i);
    bar_sync(2 + (ct >> 7), 128);
  }
  if (leader) mbar_arrive(bars + B_WFREE);
  ring_task<false>(s, q, o, ec, leader, wg);
}

__global__ void __launch_bounds__(640, 1) fused_kernel(const __grid_constant__ Maps maps) {
  extern __shared__ __align__(1024) uint8_t smem_raw[];
  if (threadIdx.x == 512) {
    asm volatile("prefetch.tensormap [%0];" ::"l"((uint64_t)&maps.x[blockIdx.x >> 6]) : "memory");
    asm volatile("prefetch.tensormap [%0];" ::"l"((uint64_t)&maps.w[blockIdx.x >> 6]) : "memory");
  }
  if (s2u(smem_raw) != sb) __trap();
  const int tid = threadIdx.x, warp = __shfl_sync(0xffffffffu, tid >> 5, 0);
  const int wg = warp >> 2;
  const int hp = blockIdx.x & 7, rb = (blockIdx.x >> 3) & 7, br = blockIdx.x >> 6;
  auto load_chunk = [&](int kc) {
    const int st = kc >= 7 ? kc - 7 : kc;
    const uint32_t a = sb + st * G_STAGE, fb = bars + B_GFULL + 8 * st;
    mbar_expect(fb, 16384 + 3 * 32 * 112);
    tma2d(a, &maps.x[br], kc * 32, rb * 256, fb);
    tma3d(a + 16384, &maps.w[br], hp * 56, kc * 32, 0, fb);
  };
  auto fill_gap = [&](int kc) {
    const int lane = tid & 31;
    const uint8_t* src = maps.in[3 * br + 1] + (size_t)(kc * 32 + lane) * (3 * DM * 2) + (2 * DM + hp * 56 + 40) * 2;
    const uint32_t d = sb + 16384 + lane * 128 + ((7 ^ (lane & 7)) << 4) + (kc >= 7 ? kc - 7 : kc) * G_STAGE;
    asm volatile("cp.async.cg.shared.global [%0], [%1], 16;" ::"r"(d), "l"(src + 16) : "memory");
    asm volatile("cp.async.cg.shared.global [%0], [%1], 16;" ::"r"(d + 4096), "l"(src) : "memory");
    asm volatile("cp.async.commit_group;" ::: "memory");
  };
  if (warp == 19) { fill_gap(0); fill_gap(1); fill_gap(2); }
  if (warp == 16) {
    if (tid == 512) {
      for (int i = 0; i < 7; i++) mbar_init(bars + B_GFULL + 8 * i, 2);
      INIT_FENCE();
    }
    __syncwarp();
    load_chunk(0);
  } else if (tid == 0) {
    for (int i = 0; i < 7; i++) { mbar_init(bars + B_GEMPTY + 8 * i, 4); mbar_init(bars + B_OPA + 8 * i, 3); }
    INIT_FENCE();
  } else if (tid == 32) {
    for (int i = 0; i < 7; i++) { mbar_init(bars + B_OPB + 8 * i, 1); mbar_init(bars + B_OPW + 8 * i, 2); }
    INIT_FENCE();
  } else if (tid == 64) {
    for (int i = 0; i < 4; i++) { mbar_init(bars + B_RFULL + 8 * i, 1); mbar_init(bars + B_REMPTY + 8 * i, 4); mbar_init(bars + B_FIN + 8 * i, 4); mbar_init(bars + B_FINB + 8 * i, 4); }
    INIT_FENCE();
  } else if (tid == 96) {
    for (int i = 0; i < 7; i++) mbar_init(bars + B_OPFREE + 8 * i, 2);
    mbar_init(bars + B_WIN, 1); mbar_init(bars + B_EPI, 16); mbar_init(bars + B_LOCAL, 5); mbar_init(bars + B_WFREE, 5);
    mbar_init(bars + B_NEAR, 1); mbar_init(bars + B_GLAST, 1); mbar_init(bars + B_EPIKV, 4); mbar_init(bars + B_EPIKV + 8, 4);
    mbar_init(bars + B_WIN2, 1); mbar_init(bars + B_PACK, 1); mbar_init(bars + B_RING4, 2); mbar_init(bars + B_END, 4); mbar_init(bars + B_ALLFIN, 16); mbar_init(bars + B_TICK, 1); mbar_init(bars + B_PACKED, 1); mbar_init(bars + B_L0, 1);
    sts32(bars + B_CONST, 0x3C003C00u); sts32(bars + B_CONST + 4, 0x11141114u); sts32(bars + W_SEEN, 0);
    INIT_FENCE();
  }
  __syncthreads();

  const int eB = br ^ 1;
  const int tile_o = rb * 4 + (hp & 3), nq = (hp >> 2) + 2 * br;
  auto gq = [&](int b, int e) { return g_q + (size_t)(b * 16 + hp * 2 + e) * (SEQ * 64); };
  auto gkv = [&](int b, int e) { return g_kv + (size_t)(b * 16 + hp * 2 + e) * (SEQ * 128); };

  if (warp >= 16) {
    asm volatile("setmaxnreg.dec.sync.aligned.u32 32;");
    {
      const int pw = warp - 16;
      if (pw == 0) {
#pragma unroll 1
        for (int kc = 1; kc < 14; kc++) {
          if (kc >= LOOK) mbar_wait(bars + B_GFULL + 8 * ((kc - LOOK) % 7), (kc - LOOK) / 7);
          if (kc >= 7) mbar_wait(bars + B_GEMPTY + 8 * (kc - 7), 0);
          load_chunk(kc);
        }
        mbar_arrive_e(bars + B_GLAST);
      } else if (pw == 3) {
#pragma unroll 1
        for (int kc = 3; kc < 14 + 3; kc++) {
          asm volatile("cp.async.wait_group 2;" ::: "memory");
          fence_async_smem();
          __syncwarp();
          mbar_arrive_e(bars + B_GFULL + 8 * (kc >= 10 ? kc - 10 : kc - 3));
          if (kc >= 7 && kc < 14) mbar_wait(bars + B_GEMPTY + 8 * (kc - 7), 0);
          if (kc < 14) fill_gap(kc); else asm volatile("cp.async.commit_group;" ::: "memory");
        }
      }
      const unsigned epoch = __shfl_sync(0xffffffffu, ld_flag(g_epoch + blockIdx.x), 0) + 1;
      const int lane = tid & 31;
      auto load_wo = [&](int b, int c, int h) {
        const uint32_t fb = bars + (b ? B_OPW : B_OPA) + 8 * c;
        mbar_expect(fb, 8192);
        if (b) bulk_ld(wo_addr(1, c, h), g_wo + ((nq * 7 + c) * 2 + h) * 8192, 8192, fb);
        else tma2d(wo_addr(0, c, h), &maps.wo[0], nq * 112 + h * 64, c * 64, fb);
      };
      auto load_o = [&](int b, int c) {
        const uint32_t fb = bars + (b ? B_OPB : B_OPA) + 8 * c;
        mbar_expect(fb, 8192);
        bulk_ld(sb + c * SLOT + 16384, g_o + (size_t)(b * 32 + tile_o) * (DM * 128) + c * 8192, 8192, fb);
      };
      auto tile_of = [&](int b, int w) { return b * 32 + rb * 4 + (b ? w : (w >> 1) + (br ? 0 : 2)); };
      auto dst_o = [&](int b, int w) { return g_o + (size_t)tile_of(b, w) * (DM * 128) + (hp * 2 + (b ? eB : (w & 1))) * (DH * 128); };
      auto cnt_o = [&](int b, int w) { return g_cnt_o + tile_of(b, w) * 32; };
      auto store_o = [&](int b, int w) {
        bulk_st(dst_o(b, w), b ? sb + OFF_QB + w * 4096 : qa_of(br, w), DH * 128);
        BULK_COMMIT();
      };
      auto publish_rest = [&]() {
        mbar_wait(bars + B_EPI, 0);
#pragma unroll 1
        for (int i = 0; i < 4; i++) {
          if (br && i == 2) wait_tick();
          bulk_st(gkv(br, i & 1) + rb * 32768 + (i >> 1) * 8192, sb + 16384 + (i & 1) * WIN + (i >> 1) * 8192, 8192);
        }
        if (!br) {
          bulk_st(gq(0, 0) + rb * 16384, sb + OFF_Q, 8192);
          bulk_st(gq(0, 1) + rb * 16384, sb + OFF_Q + 16384, 8192);
        }
        BULK_COMMIT();
        BULK_WAIT(0);
        mbar_arrive_e(bars + B_LOCAL);
        publish(g_flag + blockIdx.x * 32, 1, epoch);
      };
      const uint32_t lastpar = br ^ 1;
      if (pw == 0) {
        poll_mask(flag_of(blockIdx.x, 1, br ? (rb + 1) & 7 : 16), epoch, 1);
        unsigned seen = 1u << ((rb + br) & 7);
        mbar_wait(bars + B_EPI, 0);
        if (!br) {
          asm volatile("{.reg .pred e; elect.sync _|e, 0xffffffff;\n@e mbarrier.expect_tx.shared.b64 [%0], 16384;}" ::"r"(bars + B_RFULL) : "memory");
          bulk_ld(sb + OFF_QB, gq(1, 1) + rb * 16384, 16384, bars + B_RFULL);
        }
        const int half = 16 - 2 * br;
        int tprev = ((rb + br) & 7) * 4 + 3;
#pragma unroll 1
        for (int i = 0; i <= 2 * half; i++) {
          const int j = i >= half ? i - half : i, blk = (rb + br + (j >> 1)) & 7, tl = blk * 4 + (i & 1) + (i >= half ? 0 : 2);
          const unsigned need = 1u << (blk + (i >= half ? 8 : 0));
          if (!(seen & need)) {
#pragma unroll 1
            for (int t = 0; t < (1 << 24) && !(seen & need); t++) {
              unsigned v;
              asm volatile("ld.volatile.shared.u32 %0, [%1];" : "=r"(v) : "r"(bars + W_SEEN) : "memory");
              seen = __shfl_sync(0xffffffffu, v, 0);
            }
            asm volatile("fence.proxy.async.global;" ::: "memory");
          }
          const uint32_t fb = bars + B_RFULL + 8 * (i & 3), d = sb + OFF_RING + (i & 3) * 8192;
          asm volatile("{.reg .pred p, e; .reg .u32 n;\n"
                       "mov.u32 n, 0;\n"
                       "W%=: mbarrier.try_wait.parity.shared.b64 p, [%1+32], %4; add.u32 n, n, 1; setp.ge.or.u32 p, n, 262144, p; @!p bra W%=;\n"
                       "elect.sync _|e, 0xffffffff;\n"
                       "@e mbarrier.arrive.expect_tx.shared.b64 _, [%1], 8192;\n"
                       "@e cp.async.bulk.shared::cluster.global.mbarrier::complete_tx::bytes [%0+4096], [%3], 4096, [%1];\n"
                       "@e cp.async.bulk.shared::cluster.global.mbarrier::complete_tx::bytes [%0], [%2], 4096, [%1];}"
                       ::"r"(d), "r"(fb), "l"(gkv(1, eB) + tprev * 8192 + 4096), "l"(gkv(1, eB) + tl * 8192), "r"(((i >> 2) & 1) ^ 1) : "memory");
          tprev = tl;
          if (br && i < 4 * NLOC + 4) mbar_arrive_e(bars + B_TICK);
          if (i == 3) mbar_arrive_e(bars + B_RING4);
        }
        mbar_wait(bars + B_PACKED, 0);
        asm volatile("fence.proxy.async.global;" ::: "memory");
        mbar_arrive_e(bars + B_NEAR);
        load_wo(1, 0, 0);
        mbar_wait(bars + B_REMPTY + 8, lastpar);
        load_wo(1, 0, 1);
        mbar_wait(bars + B_REMPTY + 16, lastpar);
        load_wo(1, 1, 0);
        mbar_wait(bars + B_REMPTY + 24, lastpar);
        load_wo(1, 1, 1);
      } else if (pw == 1) {
        unsigned* fl = g_flag + blockIdx.x * 32;
        mbar_wait_lazy(bars + B_GLAST, 0);
        const uint32_t l = sb + 16384;
#pragma unroll 1
        for (int t = 3; t >= 2; t--) {
          mbar_wait(bars + B_EPIKV + 8 * (t & 1), 0);
          bulk_st(gkv(br, 0) + rb * 32768 + t * 8192, l + t * 8192, 8192);
          if (!br || t == 3) bulk_st(gkv(br, 1) + rb * 32768 + t * 8192, l + WIN + t * 8192, 8192);
          BULK_COMMIT();
        }
        BULK_WAIT(0);
        mbar_arrive_e(bars + B_L0);
        publish(fl, 0, epoch);
        mbar_wait(bars + B_RING4, 0);
        publish_rest();
#pragma unroll 1
        for (int w = 0; w < 4; w++) {
          if (w == 0) mbar_wait_lazy(bars + B_FIN + 24, 0);
          mbar_wait(bars + B_FIN + 8 * (3 - w), 0);
          store_o(0, 3 - w);
        }
        BULK_WAIT(0);
        mbar_arrive_e(bars + B_WFREE);
        release_gpu();
#pragma unroll 1
        for (int w = 0; w < 4; w++) signal(cnt_o(0, w));
      } else if (pw == 2) {
        if (br) {
          mbar_wait_lazy(bars + B_GLAST, 0);
          mbar_wait(bars + B_L0, 0);
          mbar_wait(bars + B_EPI, 0);
          bulk_st(gkv(1, 1) + rb * 32768 + 16384, sb + 16384 + WIN + 16384, 8192);
          bulk_st(gq(1, 1) + rb * 16384, sb + OFF_Q + 16384, 16384);
          BULK_COMMIT();
          BULK_WAIT(0);
          publish(g_flag + blockIdx.x * 32, 2, epoch);
          mbar_arrive_e(bars + B_RING4);
          mbar_wait(bars + B_LOCAL, 0);
          poll_mask(flag_of(blockIdx.x, 0, 8 + ((lane & 1) && rb ? rb - 1 : rb)), epoch, 3);
          mbar_expect(bars + B_WIN, 2 * WIN + 16384);
#pragma unroll 1
          for (int e = 0; e < 2; e++) {
            bulk_ld(sb + OFF_Q + e * 8192, gq(0, e) + rb * 16384, 8192, bars + B_WIN);
#pragma unroll 1
            for (int i = 0; i < 6; i += 2) {
              if (i != 2) wait_tick();
              bulk_ld(sb + e * WIN + i * 8192, (rb || i == 4) ? gkv(0, e) + (rb * 4 - 4 + i) * 8192 : g_zero, 16384, bars + B_WIN);
            }
          }
        } else {
          mbar_wait_lazy(bars + B_GLAST, 0);
#pragma unroll 1
          for (int t = 1; t >= 0; t--) {
            if (rb && t) poll_mask(g_flag + (blockIdx.x - 8) * 32, epoch, 1);
            if (t) mbar_wait(bars + B_EPIKV + 8, 0);
            const uint32_t fb = bars + (t ? B_WIN : B_WIN2);
            mbar_expect(fb, 16384);
#pragma unroll 1
            for (int e = 0; e < 2; e++) bulk_ld(sb + e * WIN + t * 8192, rb ? gkv(0, e) + (rb * 4 - 2 + t) * 8192 : g_zero, 8192, fb);
          }
          mbar_arrive_e(bars + B_RING4);
          mbar_wait_lazy(bars + B_LOCAL, 0);
        }
        mbar_wait_lazy(bars + B_WFREE, 0);
#pragma unroll 1
        for (int c = 0; c < 7; c++) { __nanosleep(br ? WPACE : APACE); load_wo(0, c, 0); load_wo(0, c, 1); }
        poll_lazy(g_cnt_o + tile_o * 32, epoch * 16);
#pragma unroll 1
        for (int c = 0; c < 7; c++) { __nanosleep(WPACE / 2); load_o(0, c); }
      }
      if (pw == 3) {
        const unsigned* fl = flag_of(blockIdx.x, 1, lane & 15) + ((br || (lane & 8)) ? 0 : 16);
        mbar_wait(bars + B_L0, 0);
        unsigned m = 0;
#pragma unroll 1
        for (int t = 0; t < (1 << 19) && m != 0xFFFFFFFFu; t++) {
          m = __ballot_sync(0xffffffffu, (int)(ld_flag(fl) - epoch) >= 0);
          asm volatile("st.volatile.shared.u32 [%0], %1;" ::"r"(bars + W_SEEN), "r"(m) : "memory");
          __nanosleep((m & 0xFF) == 0xFF ? 500 : 100);
        }
      }
      if (pw == 3) {
        mbar_wait_lazy(bars + B_LOCAL, 0);
#pragma unroll 1
        for (int i = 0; i < 28; i++) *(uint4*)(dst_o(1, i / 7) + (i % 7) * 512 + lane * 16) = make_uint4(~0u, ~0u, ~0u, ~0u);
        __syncwarp();
      }
      if (pw == 3 && blockIdx.x < 56) {
        const int pc = blockIdx.x >> 1;
        mbar_wait_lazy(bars + B_LOCAL, 0);
        mbar_expect(bars + B_PACK, 8192);
        tma2d(sb + OFF_RING + 6 * 8192, &maps.wo[1], (pc / 7) * 112 + (blockIdx.x & 1) * 64, (pc % 7) * 64, bars + B_PACK);
        mbar_wait_lazy(bars + B_PACK, 0);
        bulk_st(g_wo + blockIdx.x * 8192, sb + OFF_RING + 6 * 8192, 8192);
        BULK_COMMIT();
        BULK_WAIT(0);
      }
      if (pw == 3) {
        release_gpu();
        signal(g_cnt_w);
        mbar_wait_lazy(bars + B_WFREE, 0);
        poll_lazy(g_cnt_w, epoch * 128);
        mbar_arrive_e(bars + B_PACKED);
#pragma unroll 1
        for (int c = 0; c < 7; c++) mbar_expect(bars + B_OPB + 8 * c, 8192);
      }
      mbar_wait_lazy(bars + B_NEAR, 0);
      asm volatile("fence.proxy.async.global;" ::: "memory");
      mbar_wait(bars + B_FINB + 8 * pw, 0);
      store_o(1, pw);
      signal(cnt_o(1, pw));
      asm volatile("cp.async.bulk.wait_group.read 0;" ::: "memory");
      mbar_arrive_e(bars + B_END);
      if (pw == 2) {
        mbar_wait(bars + B_END, 0);
        load_wo(1, 2, 0);
        load_wo(1, 2, 1);
        g_epoch[blockIdx.x] = epoch;
      } else if (pw == 1) {
#pragma unroll 1
        for (int c = 0; c < 4; c++) {
          mbar_wait(bars + B_OPFREE + 8 * c, 0);
          load_wo(1, c + 3, 0);
          load_wo(1, c + 3, 1);
        }
      } else if (pw == 3) {
        poll_mask(g_cnt_o + (32 + tile_o) * 32, epoch * 16, 1);
        const uint8_t* src = g_o + (size_t)(32 + tile_o) * (DM * 128);
#pragma unroll
        for (int c = 0; c < 7; c++) {
          mbar_wait(bars + B_OPFREE + 8 * c, 0);
          bulk_ld(sb + c * SLOT + 16384, src + c * 8192, 8192, bars + B_OPB + 8 * c);
        }
      }
      validate();
    }
  } else {
  asm volatile("setmaxnreg.inc.sync.aligned.u32 112;");
  const bool leader = tid == wg * 160;
  {
    float ax[32], ay[52];
    const uint32_t da0 = mkdesc(sb + wg * 4096), db0 = mkdesc(sb + 16384) + (255u << 16);
    mbar_wait(bars + B_GFULL, 0);
    WG_FENCE();
    wgmma_g0(ay, da0, db0 + 256); wgmma_g0(ax, da0, db0);
    wgmma_g(ay, da0 + 2, db0 + 256 + 128); wgmma_g(ax, da0 + 2, db0 + 128);
    WG_COMMIT();
#pragma unroll 1
    for (int kc = 1; kc < 14; kc++) {
      const int st = kc >= 7 ? kc - 7 : kc;
      if (kc == 12 && wg < 3) {
        WG_WAIT(0);
        if (leader) mbar_arrive(bars + B_GEMPTY + 8 * (st - 1));
        bar_sync(8 + wg, 256);
      }
      mbar_wait(bars + B_GFULL + 8 * st, kc >= 7);
      const uint32_t db = db0 + st * (G_STAGE / 16), da = da0 + st * (G_STAGE / 16);
      WG_FENCE();
      wgmma_g(ay, da, db + 256); wgmma_g(ax, da, db);
      wgmma_g(ay, da + 2, db + 256 + 128); wgmma_g(ax, da + 2, db + 128);
      WG_COMMIT();
      if (kc == 13 && wg > 0) asm volatile("bar.arrive %0, 256;" ::"r"(7 + wg) : "memory");
      WG_WAIT(1);
      if (leader && !(kc == 12 && wg < 3)) mbar_arrive(bars + B_GEMPTY + 8 * (st ? st - 1 : 6));
    }
    mbar_wait(bars + B_GEMPTY + 8 * 4, 1);
    WG_WAIT(0);
    pin(ax); pin(ay);
    bar_sync(2 + wg, 128);
    const int ct = cold_tid(), t = ct & 3;
    const uint32_t lm = lm_offset(ct);
    auto put = [&](const uint32_t (&w)[14], uint32_t b0, uint32_t b1, uint32_t aux0, uint32_t aux1) {
      const uint32_t x0 = (t & 1) ? 0u : aux0, x1 = (t & 1) ? 0u : aux1;
      stsm4(b0 + lm, w[0], w[1], w[2], w[3]);
      stsm4(b0 + (lm ^ 32), w[4], w[5], t < 2 ? w[6] : x0, t < 2 ? w[7] : x1);
      stsm4(b1 + lm, w[8], w[9], w[10], w[11]);
      stsm4(b1 + (lm ^ 32), w[12], w[13], t < 2 ? x0 : w[6], t < 2 ? x1 : w[7]);
    };
    uint32_t w[14];
    const bool sw0 = (SWG >> (((ct >> 5) & 3) * 2)) & 1, sw1 = (SWG >> (((ct >> 5) & 3) * 2 + 1)) & 1;
    const uint32_t kv = sb + (2 + wg) * 8192;
#pragma unroll
    for (int i = 0; i < 14; i++) w[i] = mul_bf16x2(pack_bf16(ay[2 * i], ay[2 * i + 1]), (((i & 1) ? sw1 : sw0) ? BF_M70 : BF_P70) * 0x10001u);
    put(w, kv, kv + WIN, sw0 ? BF_M70 * 0x10001u : BF_P70, sw1 ? BF_M70 * 0x10001u : BF_P70);
#pragma unroll
    for (int i = 0; i < 14; i++)
      w[i] = i < 10 ? pack_bf16(ay[32 + 2 * i], ay[33 + 2 * i]) : i < 12 ? pack_bf16(ay[8 + 2 * i], ay[9 + 2 * i]) : pack_bf16(ax[4 + 2 * i], ax[5 + 2 * i]);
    put(w, kv + 4096, kv + WIN + 4096, BF_ONE, BF_ONE);
    if (wg >= 2) {
      fence_async_smem();
      __syncwarp();
      if ((ct & 31) == 0) mbar_arrive(bars + B_EPIKV + 8 * (wg & 1));
    }
#pragma unroll
    for (int i = 0; i < 14; i++) w[i] = pack_bf16(ax[2 * i] * (QSCALE * M70), ax[2 * i + 1] * (QSCALE * M70));
    put(w, sb + (br ? OFF_QB : OFF_Q) + wg * 4096, sb + OFF_Q + 16384 + wg * 4096, 0, 0);
    fence_async_smem();
    __syncwarp();
    if ((ct & 31) == 0) mbar_arrive(bars + B_EPI);
    if (br) bar_sync(2 + wg, 128); else mbar_wait(bars + B_EPI, 0);
  }
  attention(leader, warp);
  {
    if (wg & 1) proj<1>((wg >> 1) ^ 1, maps.out, leader); else proj<0>((wg >> 1) ^ 1, maps.out, leader);
  }
  }
}

typedef CUresult (*EncodeFn)(CUtensorMap*, CUtensorMapDataType, cuuint32_t, void*, const cuuint64_t*, const cuuint64_t*,
                             const cuuint32_t*, const cuuint32_t*, CUtensorMapInterleave, CUtensorMapSwizzle,
                             CUtensorMapL2promotion, CUtensorMapFloatOOBfill);

void make_map(EncodeFn enc, CUtensorMap* m, const void* ptr, int rank, const cuuint64_t* dims, const cuuint64_t* strides,
              const cuuint32_t* box, CUtensorMapSwizzle sw) {
  cuuint32_t es[3] = {1, 1, 1};
  enc(m, CU_TENSOR_MAP_DATA_TYPE_BFLOAT16, rank, const_cast<void*>(ptr), dims, strides, box, es, CU_TENSOR_MAP_INTERLEAVE_NONE, sw,
      CU_TENSOR_MAP_L2_PROMOTION_L2_128B, CU_TENSOR_MAP_FLOAT_OOB_FILL_NONE);
}

}

extern "C" void kernel_launch(void* const* d_in, const int* in_sizes, int n_in, void* d_out, int out_size) {
  (void)in_sizes; (void)n_in; (void)out_size;
  void* fn = nullptr;
  cudaDriverEntryPointQueryResult qr;
  cudaGetDriverEntryPoint("cuTensorMapEncodeTiled", &fn, cudaEnableDefault, &qr);
  EncodeFn enc = (EncodeFn)fn;
  Maps maps;
  for (int i = 0; i < 6; i++) maps.in[i] = (const uint8_t*)d_in[i];
  for (int b = 0; b < 2; b++) {
    { cuuint64_t d[2] = {DM, SEQ}, s[1] = {DM * 2}; cuuint32_t bx[2] = {32, 256};
      make_map(enc, &maps.x[b], d_in[3 * b], 2, d, s, bx, CU_TENSOR_MAP_SWIZZLE_64B); }
    { cuuint64_t d[3] = {DM, DM, 3}, s[2] = {3 * DM * 2, DM * 2}; cuuint32_t bx[3] = {56, 32, 3};
      make_map(enc, &maps.w[b], d_in[3 * b + 1], 3, d, s, bx, CU_TENSOR_MAP_SWIZZLE_128B); }
    { cuuint64_t d[2] = {DM, DM}, s[1] = {DM * 2}; cuuint32_t bx[2] = {64, 64};
      make_map(enc, &maps.wo[b], d_in[3 * b + 2], 2, d, s, bx, CU_TENSOR_MAP_SWIZZLE_128B); }
  }
  maps.out = (uint8_t*)d_out;
  cudaFuncSetAttribute(fused_kernel, cudaFuncAttributeMaxDynamicSharedMemorySize, SMEM_BYTES);
  fused_kernel<<<128, 640, SMEM_BYTES>>>(maps);
}
```
